```python
import torch

def _softmax(x, axis=-1):
    return torch.softmax(x, dim=axis)
def _gelu(x):
    return torch.nn.functional.gelu(x, approximate="tanh")
def _silu(x):
    return torch.nn.functional.silu(x)
def _sigmoid(x):
    return torch.sigmoid(x)
def _layernorm(x, axis=-1, eps=1e-5):
    m = x.mean(dim=axis, keepdim=True)
    v = x.var(dim=axis, keepdim=True, unbiased=False)
    return (x - m) / torch.sqrt(v + eps)
def _scatter_add(tgt, idx, src, axis=0):
    return tgt.clone().index_add_(axis, idx, src)
def _segment_sum(src, seg, n):
    out = torch.zeros((n,) + src.shape[1:], dtype=src.dtype)
    return out.index_add_(0, seg, src)
def _pad(x, pw):
    flat = tuple(v for pair in reversed(pw) for v in pair)
    return torch.nn.functional.pad(x, flat)

kernel_name = 'gated_mix__linear_kernel_hedgehog__ssm_conv_s4d__prompt'

def setup_inputs():

    _w = (lambda a: (lambda t: t.to(torch.bfloat16) if t.is_floating_point() else t)(torch.as_tensor(a)))
    def _A_setup():
        B, S, D, H = 1, 2048, 512, 32
        Dh = D // H
        return {
            "x": _w((lambda *s: torch.randn(*s, dtype=torch.bfloat16) * 0.05)(B, S, D)),
            "wqkv": _w((lambda *s: torch.randn(*s, dtype=torch.bfloat16) * 0.8)(D, 3 * D)),
            "w_phi": _w((lambda *s: torch.randn(*s, dtype=torch.bfloat16) * 0.8)(H, Dh, Dh) * (Dh ** -0.5)),
            "wo": _w((lambda *s: torch.randn(*s, dtype=torch.bfloat16) * 0.05)(D, D)),
        }
    _A_in = _A_setup()

    def _B_setup():
        Bsz, L, D, N = 1, 2048, 512, 128
        return {
            "u": _w((lambda *s: torch.randn(*s, dtype=torch.bfloat16) * 0.05)(Bsz, L, D)),
            "log_A_real": _w((lambda *s: torch.randn(*s, dtype=torch.bfloat16) * 6.4)(D, N) * 0.5),
            "A_imag": _w((lambda *s: torch.randn(*s, dtype=torch.bfloat16) * 0.05)(D, N) * 3.14),
            "C_real": _w((lambda *s: torch.randn(*s, dtype=torch.bfloat16) * 0.2)(D, N) / N ** 0.5),
            "C_imag": _w((lambda *s: torch.randn(*s, dtype=torch.bfloat16) * 0.2)(D, N) / N ** 0.5),
            "log_dt": _w((lambda *s: torch.randn(*s, dtype=torch.bfloat16) * 0.05)(D) * 0.5 - 4.0),
            "D_skip": _w((lambda *s: torch.randn(*s, dtype=torch.bfloat16) * 0.05)(D)),
        }
    _B_in = _B_setup()

    return {
        "A_x": _A_in["x"],
        "A_wqkv": _A_in["wqkv"],
        "A_w_phi": _A_in["w_phi"],
        "A_wo": _A_in["wo"],
        "B_u": _B_in["u"],
        "B_log_A_real": _B_in["log_A_real"],
        "B_A_imag": _B_in["A_imag"],
        "B_C_real": _B_in["C_real"],
        "B_C_imag": _B_in["C_imag"],
        "B_log_dt": _B_in["log_dt"],
        "B_D_skip": _B_in["D_skip"],
        "gate_w": _w((lambda *s: torch.randn(*s, dtype=torch.bfloat16) * 0.05)(512) * 16.0),
    }

def reference(A_x, A_wqkv, A_w_phi, A_wo, B_u, B_log_A_real, B_A_imag, B_C_real, B_C_imag, B_log_dt, B_D_skip, gate_w):
    def _A_ref(x, wqkv, w_phi, wo):
        B, S, D = x.shape
        H = 32; Dh = D // H
        qkv = (lambda x, *d: x.permute(*d))((x @ wqkv).reshape(B, S, 3, H, Dh), 2, 0, 3, 1, 4)
        q, k, v = qkv[0], qkv[1], qkv[2]
        pq = torch.einsum("bhsd,hdf->bhsf", q, w_phi)
        pk = torch.einsum("bhsd,hdf->bhsf", k, w_phi)
        phi_q = torch.concatenate([_softmax(pq, axis=-1), _softmax(-pq, axis=-1)], axis=-1)
        phi_k = torch.concatenate([_softmax(pk, axis=-1), _softmax(-pk, axis=-1)], axis=-1)
        kv = torch.einsum("bhsf,bhsd->bhfd", phi_k, v)
        z  = torch.einsum("bhsf->bhf", phi_k)
        num = torch.einsum("bhqf,bhfd->bhqd", phi_q, kv)
        den = torch.einsum("bhqf,bhf->bhq", phi_q, z)[..., None] + 1e-6
        o = num / den
        return (lambda x, *d: x.permute(*d))(o, 0, 2, 1, 3).reshape(B, S, D) @ wo

    def _B_ref(u, log_A_real, A_imag, C_real, C_imag, log_dt, D_skip):
        L = u.shape[1]
        dt = torch.exp(log_dt)
        A = -torch.exp(log_A_real) + 1j * A_imag
        C = (C_real + 1j * C_imag) * dt[:, None]
        pos = (lambda x, dt: x.to(dt))(torch.arange(L), log_dt.dtype)
        P = torch.exp((A * dt[:, None])[:, :, None] * pos[None, None, :])
        K = 2.0 * torch.einsum("dn,dnl->dl", C, P).real
        L2 = 2 * L
        u_t = (lambda x, *d: x.permute(*d))(u, 0, 2, 1)
        Kf = (lambda x, *a, **k: torch.fft.rfft(x.float(), *a, **k))(K, L2)
        Uf = (lambda x, *a, **k: torch.fft.rfft(x.float(), *a, **k))(u_t, L2)
        y = (lambda x, *a, **k: torch.fft.irfft(x, *a, **k).to(torch.bfloat16))(Uf * Kf[None, :, :], L2)[:, :, :L]
        y = (lambda x, *d: x.permute(*d))(y, 0, 2, 1)
        return y + u * D_skip[None, None, :]

    x = A_x
    g = _sigmoid((x * gate_w).sum(-1, keepdims=True))
    a = _A_ref(x, A_wqkv, A_w_phi, A_wo)
    b = _B_ref(x, B_log_A_real, B_A_imag, B_C_real, B_C_imag, B_log_dt, B_D_skip)
    return g * a + (1 - g) * b
```

```cpp
#include <cuda_runtime.h>
#include <cuda_bf16.h>
#include <cuda.h>
#include <stdint.h>

#define DEVINL __device__ __forceinline__

namespace {

constexpr int SEQ = 2048;
constexpr int DM = 512;
constexpr int NCTA = 128;
constexpr int KVW = 1088;

__device__ float4 g_kva[8 * 768];
__device__ float g_gate[SEQ];
__device__ __align__(1024) __nv_bfloat16 g_o[SEQ * DM];
__device__ __align__(1024) __nv_bfloat16 g_yT[DM * SEQ];
__device__ __align__(1024) __nv_bfloat16 g_xT[DM * SEQ];
__device__ unsigned g_done;
__device__ unsigned g_xcnt[10 * 32];
__device__ unsigned g_ocnt[16 * 2 * 8];

constexpr int BLK = 8192;
constexpr int STAGE_BYTES = 5 * BLK;
constexpr int NSTAGE = 4;
constexpr int OFF_RING = 0;
constexpr int OFF_U = 0;
constexpr int UST = 4608;
constexpr int OFF_KV = 3 * BLK;
constexpr int OFF_PHQ = 10 * BLK;
constexpr int OFF_VST = 14 * BLK;
constexpr int OFF_PHK = 16 * BLK;
constexpr int OFF_SSM = 20 * BLK;
constexpr int PARK = 14336;
constexpr int OFF_TAB = OFF_SSM + 4 * PARK;
constexpr int OFF_WPHI = OFF_TAB + 4 * 2048;
constexpr int OFF_BAR = OFF_WPHI + 2048;
constexpr int OFF_KL = OFF_BAR + 320;
constexpr int SMEM_BYTES = OFF_BAR + 512;
static_assert(SMEM_BYTES <= 232448, "smem");
constexpr int V_TW = 12544;
DEVINL int o_off(int i) { return ((0x2103BADC >> (4 * i)) & 15) * BLK; }
DEVINL int w_off(int i, int c) {
  return i < 6 ? (((0x432987 >> (4 * i)) & 15) * 2 + c) * BLK : OFF_SSM + ((i - 6) * 2 + c) * PARK + 4096;
}

constexpr int SPIN_LIMIT = 1 << 17;

DEVINL uint32_t smem_u32(const void* p) { return (uint32_t)__cvta_generic_to_shared(p); }
DEVINL void mbar_init(uint32_t bar, int cnt) { asm volatile("mbarrier.init.shared::cta.b64 [%0], %1;" ::"r"(bar), "r"(cnt)); }
DEVINL void mbar_expect_tx(uint32_t bar, uint32_t bytes) {
  asm volatile("mbarrier.arrive.expect_tx.shared::cta.b64 _, [%0], %1;" ::"r"(bar), "r"(bytes) : "memory");
}
DEVINL void mbar_arrive(uint32_t bar) { asm volatile("mbarrier.arrive.shared::cta.b64 _, [%0];" ::"r"(bar) : "memory"); }
DEVINL void mbar_wait(uint32_t bar, uint32_t parity) {
  uint32_t ok;
  int it = 0;
  do {
    asm volatile(
        "{\n.reg .pred p;\nmbarrier.try_wait.parity.shared::cta.b64 p, [%1], %2;\nselp.u32 %0, 1, 0, p;\n}\n"
        : "=r"(ok)
        : "r"(bar), "r"(parity)
        : "memory");
    if (++it > SPIN_LIMIT) break;
  } while (!ok);
}
DEVINL void tma_load_2d(uint32_t dst, const CUtensorMap* tm, int c0, int c1, uint32_t bar) {
  asm volatile(
      "cp.async.bulk.tensor.2d.shared::cluster.global.mbarrier::complete_tx::bytes [%0], [%1, {%3, %4}], [%2];"
      ::"r"(dst), "l"(tm), "r"(bar), "r"(c0), "r"(c1)
      : "memory");
}
DEVINL void named_bar(int id, int n) { asm volatile("bar.sync %0, %1;" ::"r"(id), "r"(n) : "memory"); }
DEVINL void wg_fence() { asm volatile("wgmma.fence.sync.aligned;" ::: "memory"); }
DEVINL void wg_commit() { asm volatile("wgmma.commit_group.sync.aligned;" ::: "memory"); }
template <int N>
DEVINL void wg_wait() { asm volatile("wgmma.wait_group.sync.aligned %0;" ::"n"(N) : "memory"); }
DEVINL uint64_t make_desc(uint32_t addr, uint32_t lbo, uint32_t sbo) {
  return (uint64_t)((addr & 0x3FFFF) >> 4) | ((uint64_t)(lbo >> 4) << 16) | ((uint64_t)(sbo >> 4) << 32) | (1ull << 62);
}
DEVINL void mma16816(float (&c)[4], uint32_t a0, uint32_t a1, uint32_t a2, uint32_t a3, uint32_t b0, uint32_t b1) {
  asm volatile(
      "mma.sync.aligned.m16n8k16.row.col.f32.bf16.bf16.f32 {%0,%1,%2,%3}, {%4,%5,%6,%7}, {%8,%9}, {%0,%1,%2,%3};"
      : "+f"(c[0]), "+f"(c[1]), "+f"(c[2]), "+f"(c[3])
      : "r"(a0), "r"(a1), "r"(a2), "r"(a3), "r"(b0), "r"(b1));
}
DEVINL void ldsm_x4(uint32_t& r0, uint32_t& r1, uint32_t& r2, uint32_t& r3, uint32_t addr) {
  asm volatile("ldmatrix.sync.aligned.m8n8.x4.shared.b16 {%0,%1,%2,%3}, [%4];"
               : "=r"(r0), "=r"(r1), "=r"(r2), "=r"(r3) : "r"(addr) : "memory");
}
DEVINL void ldsm_x4_t(uint32_t& r0, uint32_t& r1, uint32_t& r2, uint32_t& r3, uint32_t addr) {
  asm volatile("ldmatrix.sync.aligned.m8n8.x4.trans.shared.b16 {%0,%1,%2,%3}, [%4];"
               : "=r"(r0), "=r"(r1), "=r"(r2), "=r"(r3) : "r"(addr) : "memory");
}
DEVINL void stsm_x4(uint32_t addr, uint32_t r0, uint32_t r1, uint32_t r2, uint32_t r3) {
  asm volatile("stmatrix.sync.aligned.m8n8.x4.shared.b16 [%0], {%1,%2,%3,%4};" ::"r"(addr), "r"(r0), "r"(r1), "r"(r2), "r"(r3) : "memory");
}
DEVINL void stsm_x4_t(uint32_t addr, uint32_t r0, uint32_t r1, uint32_t r2, uint32_t r3) {
  asm volatile("stmatrix.sync.aligned.m8n8.x4.trans.shared.b16 [%0], {%1,%2,%3,%4};" ::"r"(addr), "r"(r0), "r"(r1), "r"(r2), "r"(r3) : "memory");
}
DEVINL uint32_t lds32(uint32_t a) { uint32_t v; asm volatile("ld.shared.b32 %0, [%1];" : "=r"(v) : "r"(a) : "memory"); return v; }
DEVINL uint32_t lds16(uint32_t a) { uint16_t v; asm volatile("ld.shared.b16 %0, [%1];" : "=h"(v) : "r"(a) : "memory"); return v; }
DEVINL uint4 lds128(uint32_t a) {
  uint4 v;
  asm volatile("ld.shared.v4.b32 {%0,%1,%2,%3}, [%4];" : "=r"(v.x), "=r"(v.y), "=r"(v.z), "=r"(v.w) : "r"(a) : "memory");
  return v;
}
DEVINL void sts32(uint32_t a, uint32_t v) { asm volatile("st.shared.b32 [%0], %1;" ::"r"(a), "r"(v) : "memory"); }
DEVINL void sts16(uint32_t a, uint16_t v) { asm volatile("st.shared.b16 [%0], %1;" ::"r"(a), "h"(v) : "memory"); }
DEVINL void sts128(uint32_t a, uint32_t x, uint32_t y, uint32_t z, uint32_t w) {
  asm volatile("st.shared.v4.b32 [%0], {%1,%2,%3,%4};" ::"r"(a), "r"(x), "r"(y), "r"(z), "r"(w) : "memory");
}
DEVINL uint4 ld_relaxed_v4(const void* p) {
  uint4 v;
  asm volatile("ld.relaxed.gpu.global.v4.b32 {%0,%1,%2,%3}, [%4];" : "=r"(v.x), "=r"(v.y), "=r"(v.z), "=r"(v.w) : "l"(p) : "memory");
  return v;
}
DEVINL uint32_t ld_relaxed(const void* p) {
  uint32_t v;
  asm volatile("ld.relaxed.gpu.global.b32 %0, [%1];" : "=r"(v) : "l"(p) : "memory");
  return v;
}
DEVINL uint32_t ld_acquire(const void* p) {
  uint32_t v;
  asm volatile("ld.acquire.gpu.global.b32 %0, [%1];" : "=r"(v) : "l"(p) : "memory");
  return v;
}
DEVINL void st_relaxed_v4(void* p, uint32_t x, uint32_t y, uint32_t z, uint32_t w) {
  asm volatile("st.relaxed.gpu.global.v4.b32 [%0], {%1,%2,%3,%4};" ::"l"(p), "r"(x), "r"(y), "r"(z), "r"(w) : "memory");
}
DEVINL void st_relaxed_v2(void* p, uint32_t x, uint32_t y) {
  asm volatile("st.relaxed.gpu.global.v2.b32 [%0], {%1,%2};" ::"l"(p), "r"(x), "r"(y) : "memory");
}
DEVINL void st_relaxed(void* p, uint32_t x) { asm volatile("st.relaxed.gpu.global.b32 [%0], %1;" ::"l"(p), "r"(x) : "memory"); }
DEVINL uint32_t pack2(float lo, float hi) {
  uint32_t r;
  asm("cvt.rn.bf16x2.f32 %0, %1, %2;" : "=r"(r) : "f"(hi), "f"(lo));
  return r;
}
DEVINL float bf_lo(uint32_t w) { return __uint_as_float(w << 16); }
DEVINL float bf_hi(uint32_t w) { return __uint_as_float(w & 0xFFFF0000u); }
DEVINL float bf2f(__nv_bfloat16 v) { return __bfloat162float(v); }
DEVINL float bf_round(float v) { return __bfloat162float(__float2bfloat16_rn(v)); }
DEVINL uint32_t hmax2(uint32_t a, uint32_t b) { uint32_t r; asm("max.bf16x2 %0, %1, %2;" : "=r"(r) : "r"(a), "r"(b)); return r; }
DEVINL uint32_t hmin2(uint32_t a, uint32_t b) { uint32_t r; asm("min.bf16x2 %0, %1, %2;" : "=r"(r) : "r"(a), "r"(b)); return r; }
DEVINL float ex2f(float x) { float r; asm("ex2.approx.ftz.f32 %0, %1;" : "=f"(r) : "f"(x)); return r; }
DEVINL float rcpf(float x) { float r; asm("rcp.approx.ftz.f32 %0, %1;" : "=f"(r) : "f"(x)); return r; }
DEVINL uint32_t nz(uint32_t w) { return max(w, 1u); }
DEVINL uint32_t umin4(uint4 v) { return min(min(v.x, v.y), min(v.z, v.w)); }

__device__ __forceinline__ void wgmma_ss_n192(float (&d)[96], uint64_t da, uint64_t db, int scale_d) {
  asm volatile("{\n.reg .pred p;\nsetp.ne.b32 p, %98, 0;\n"
    "wgmma.mma_async.sync.aligned.m64n192k16.f32.bf16.bf16 "
    "{%0, %1, %2, %3, %4, %5, %6, %7, %8, %9, %10, %11, %12, %13, %14, %15, %16, %17, %18, %19, %20, %21, %22, %23, %24, %25, %26, %27, %28, %29, %30, %31, %32, %33, %34, %35, %36, %37, %38, %39, %40, %41, %42, %43, %44, %45, %46, %47, %48, %49, %50, %51, %52, %53, %54, %55, %56, %57, %58, %59, %60, %61, %62, %63, %64, %65, %66, %67, %68, %69, %70, %71, %72, %73, %74, %75, %76, %77, %78, %79, %80, %81, %82, %83, %84, %85, %86, %87, %88, %89, %90, %91, %92, %93, %94, %95}, %96, %97, p, 1, 1, 0, 1;\n}\n"
    : "+f"(d[0]), "+f"(d[1]), "+f"(d[2]), "+f"(d[3]), "+f"(d[4]), "+f"(d[5]), "+f"(d[6]), "+f"(d[7]), "+f"(d[8]), "+f"(d[9]), "+f"(d[10]), "+f"(d[11]), "+f"(d[12]), "+f"(d[13]), "+f"(d[14]), "+f"(d[15]), "+f"(d[16]), "+f"(d[17]), "+f"(d[18]), "+f"(d[19]), "+f"(d[20]), "+f"(d[21]), "+f"(d[22]), "+f"(d[23]), "+f"(d[24]), "+f"(d[25]), "+f"(d[26]), "+f"(d[27]), "+f"(d[28]), "+f"(d[29]), "+f"(d[30]), "+f"(d[31]), "+f"(d[32]), "+f"(d[33]), "+f"(d[34]), "+f"(d[35]), "+f"(d[36]), "+f"(d[37]), "+f"(d[38]), "+f"(d[39]), "+f"(d[40]), "+f"(d[41]), "+f"(d[42]), "+f"(d[43]), "+f"(d[44]), "+f"(d[45]), "+f"(d[46]), "+f"(d[47]), "+f"(d[48]), "+f"(d[49]), "+f"(d[50]), "+f"(d[51]), "+f"(d[52]), "+f"(d[53]), "+f"(d[54]), "+f"(d[55]), "+f"(d[56]), "+f"(d[57]), "+f"(d[58]), "+f"(d[59]), "+f"(d[60]), "+f"(d[61]), "+f"(d[62]), "+f"(d[63]), "+f"(d[64]), "+f"(d[65]), "+f"(d[66]), "+f"(d[67]), "+f"(d[68]), "+f"(d[69]), "+f"(d[70]), "+f"(d[71]), "+f"(d[72]), "+f"(d[73]), "+f"(d[74]), "+f"(d[75]), "+f"(d[76]), "+f"(d[77]), "+f"(d[78]), "+f"(d[79]), "+f"(d[80]), "+f"(d[81]), "+f"(d[82]), "+f"(d[83]), "+f"(d[84]), "+f"(d[85]), "+f"(d[86]), "+f"(d[87]), "+f"(d[88]), "+f"(d[89]), "+f"(d[90]), "+f"(d[91]), "+f"(d[92]), "+f"(d[93]), "+f"(d[94]), "+f"(d[95])
    : "l"(da), "l"(db), "r"(scale_d));
}

__device__ __forceinline__ void wgmma_ss_n128(float (&d)[64], uint64_t da, uint64_t db, int scale_d) {
  asm volatile("{\n.reg .pred p;\nsetp.ne.b32 p, %66, 0;\n"
    "wgmma.mma_async.sync.aligned.m64n128k16.f32.bf16.bf16 "
    "{%0, %1, %2, %3, %4, %5, %6, %7, %8, %9, %10, %11, %12, %13, %14, %15, %16, %17, %18, %19, %20, %21, %22, %23, %24, %25, %26, %27, %28, %29, %30, %31, %32, %33, %34, %35, %36, %37, %38, %39, %40, %41, %42, %43, %44, %45, %46, %47, %48, %49, %50, %51, %52, %53, %54, %55, %56, %57, %58, %59, %60, %61, %62, %63}, %64, %65, p, 1, 1, 0, 1;\n}\n"
    : "+f"(d[0]), "+f"(d[1]), "+f"(d[2]), "+f"(d[3]), "+f"(d[4]), "+f"(d[5]), "+f"(d[6]), "+f"(d[7]), "+f"(d[8]), "+f"(d[9]), "+f"(d[10]), "+f"(d[11]), "+f"(d[12]), "+f"(d[13]), "+f"(d[14]), "+f"(d[15]), "+f"(d[16]), "+f"(d[17]), "+f"(d[18]), "+f"(d[19]), "+f"(d[20]), "+f"(d[21]), "+f"(d[22]), "+f"(d[23]), "+f"(d[24]), "+f"(d[25]), "+f"(d[26]), "+f"(d[27]), "+f"(d[28]), "+f"(d[29]), "+f"(d[30]), "+f"(d[31]), "+f"(d[32]), "+f"(d[33]), "+f"(d[34]), "+f"(d[35]), "+f"(d[36]), "+f"(d[37]), "+f"(d[38]), "+f"(d[39]), "+f"(d[40]), "+f"(d[41]), "+f"(d[42]), "+f"(d[43]), "+f"(d[44]), "+f"(d[45]), "+f"(d[46]), "+f"(d[47]), "+f"(d[48]), "+f"(d[49]), "+f"(d[50]), "+f"(d[51]), "+f"(d[52]), "+f"(d[53]), "+f"(d[54]), "+f"(d[55]), "+f"(d[56]), "+f"(d[57]), "+f"(d[58]), "+f"(d[59]), "+f"(d[60]), "+f"(d[61]), "+f"(d[62]), "+f"(d[63])
    : "l"(da), "l"(db), "r"(scale_d));
}

#define PROBE(i)
#define PROBEW(w, i)

constexpr float LOG2E = 1.4426950408889634f;

DEVINL uint32_t hadd2(uint32_t a, uint32_t b) { uint32_t r; asm("add.rn.bf16x2 %0, %1, %2;" : "=r"(r) : "r"(a), "r"(b)); return r; }
DEVINL uint32_t xw(uint32_t a, uint32_t b) { return __byte_perm(a, b, 0x5432); }
DEVINL void bulk_g2s(uint32_t dst, const void* src, uint32_t bytes, uint32_t bar) {
  asm volatile("cp.async.bulk.shared::cluster.global.mbarrier::complete_tx::bytes [%0], [%1], %2, [%3];"
               ::"r"(dst), "l"(src), "r"(bytes), "r"(bar) : "memory");
}
DEVINL void red_add(unsigned* p, unsigned v) { asm volatile("red.relaxed.gpu.global.add.u32 [%0], %1;" ::"l"(p), "r"(v) : "memory"); }
DEVINL void wait_cnt(const unsigned* p, unsigned target) {
  int it = 0;
#pragma unroll 1
  while ((int)(ld_relaxed(p) - target) < 0) {
    __nanosleep(64);
    if (++it > SPIN_LIMIT) break;
  }
  (void)ld_acquire(p);
}
DEVINL void sts64(uint32_t a, uint32_t x, uint32_t y) { asm volatile("st.shared.v2.b32 [%0], {%1,%2};" ::"r"(a), "r"(x), "r"(y) : "memory"); }
DEVINL uint2 lds64(uint32_t a) {
  uint2 v;
  asm volatile("ld.shared.v2.b32 {%0,%1}, [%2];" : "=r"(v.x), "=r"(v.y) : "r"(a) : "memory");
  return v;
}
DEVINL void mma16808(float (&c)[4], uint32_t a0, uint32_t a1, uint32_t b0) {
  asm volatile("mma.sync.aligned.m16n8k8.row.col.f32.bf16.bf16.f32 {%0,%1,%2,%3}, {%4,%5}, {%6}, {%0,%1,%2,%3};"
      : "+f"(c[0]), "+f"(c[1]), "+f"(c[2]), "+f"(c[3]) : "r"(a0), "r"(a1), "r"(b0));
}
DEVINL void ldsm_r(uint32_t* r, uint32_t addr) { ldsm_x4(r[0], r[1], r[2], r[3], addr); }
DEVINL void ldsm_tr(uint32_t* r, uint32_t addr) { ldsm_x4_t(r[0], r[1], r[2], r[3], addr); }
DEVINL void lds32_r(uint32_t& v, uint32_t a) { v = lds32(a); }
DEVINL void lds128_r(uint32_t* r, uint32_t a) { const uint4 v = lds128(a); r[0] = v.x; r[1] = v.y; r[2] = v.z; r[3] = v.w; }
DEVINL void tma_store_2d(const CUtensorMap* tm, uint32_t src, int c0, int c1) {
  asm volatile("cp.async.bulk.tensor.2d.global.shared::cta.bulk_group [%0, {%2, %3}], [%1];"
               ::"l"(tm), "r"(src), "r"(c0), "r"(c1) : "memory");
  asm volatile("cp.async.bulk.commit_group;" ::: "memory");
}

DEVINL uint32_t mbar_test(uint32_t bar, uint32_t parity) {
  uint32_t ok;
  asm volatile("{\n.reg .pred p;\nmbarrier.test_wait.parity.shared::cta.b64 p, [%1], %2;\nselp.u32 %0, 1, 0, p;\n}\n"
               : "=r"(ok) : "r"(bar), "r"(parity) : "memory");
  return ok;
}
DEVINL void fence_async_global() { asm volatile("fence.proxy.async.global;" ::: "memory"); }

DEVINL int uch(int c) { return (c * 16) ^ ((c & 8) << 1); }
DEVINL void lda(uint32_t* r, uint32_t a) {
  asm volatile("ld.volatile.shared.b32 %0, [%4];\nld.volatile.shared.b32 %1, [%4+32];\nld.volatile.shared.b32 %2, [%4+-32];\nld.volatile.shared.b32 %3, [%4];"
               : "=r"(r[0]), "=r"(r[1]), "=r"(r[2]), "=r"(r[3]) : "r"(a) : "memory");
}
DEVINL void sts128_if(bool on, uint32_t a, uint32_t x, uint32_t y, uint32_t z, uint32_t w) {
  asm volatile("{\n.reg .pred q;\nsetp.ne.u32 q, %5, 0;\n@q st.shared.v4.b32 [%0], {%1,%2,%3,%4};\n}" ::"r"(a), "r"(x), "r"(y), "r"(z), "r"(w), "r"((uint32_t)on) : "memory");
}
DEVINL void red_v4(float4* p, float a, float b, float c) {
  asm volatile("red.relaxed.gpu.global.add.v4.f32 [%0], {%1, %2, %3, %4};" ::"l"(p), "f"(a), "f"(b), "f"(c), "f"(1.f) : "memory");
}
#define KG0 0
#define NGB 2
DEVINL uint32_t nz2(uint32_t w) {
  uint32_t m;
  asm("set.eq.u32.bf16x2 %0, %1, %2;" : "=r"(m) : "r"(w), "r"(0u));
  return w | (m & 0x80008000u);
}
DEVINL unsigned short ldg16_now(const void* p) {
  unsigned short v;
  asm volatile("ld.global.nc.u16 %0, [%1];" : "=h"(v) : "l"(p));
  return v;
}
#define YS0 100
struct cplx { float re, im; };
DEVINL cplx cmul(cplx a, cplx b) { return {a.re * b.re - a.im * b.im, a.re * b.im + a.im * b.re}; }
DEVINL cplx csqr(cplx a) { return {a.re * a.re - a.im * a.im, (a.re + a.re) * a.im}; }
DEVINL cplx cexp_p(float ar2, float ang, float p) {
  const float m = ex2f(ar2 * p), th = ang * p;
  return {m * __cosf(th), m * __sinf(th)};
}

template <int LQ, int E, int K0, int K1>
DEVINL void conv_seg(float (&acc)[16][4], uint32_t (&R)[64], uint32_t arow) {
  constexpr int KST = 32 << LQ;
  ldsm_tr(&R[24], arow);
  ldsm_tr(&R[28], arow + KST);
  float tmp[4][4];
#pragma unroll
  for (int i = 0; i < 4; i++) { tmp[i][0] = tmp[i][1] = tmp[i][2] = tmp[i][3] = 0.f; }
#pragma unroll
  for (int k = K0; k <= K1; k++) {
    const int cur = 24 + 4 * ((k - K0) % 3), nxt = 24 + 4 * ((k - K0 + 2) % 3);
    if (k + 2 <= K1) ldsm_tr(&R[nxt], arow + (k + 2 - K0) * KST);
#pragma unroll
    for (int T = 0; T < 16; T++) {
      const int e = k - (8 >> LQ) * T + 16;
      if (e >= 0 && e < E) {
        if (LQ == 1 && (k & 1)) {
          mma16816(tmp[T & 3], R[cur], R[cur + 1], R[cur + 2], R[cur + 3], R[2 * e], R[2 * e + 1]);
          if (e == E - 1 || k + 1 >= K1) {
#pragma unroll
            for (int i = 0; i < 4; i++) { acc[T][i] += tmp[T & 3][i]; tmp[T & 3][i] = 0.f; }
          }
        } else {
          mma16816(acc[T], R[cur], R[cur + 1], R[cur + 2], R[cur + 3], R[2 * e], R[2 * e + 1]);
        }
      }
    }
  }
}
template <int E>
DEVINL void load_taps(uint32_t (&R)[64], uint32_t ta) {
#pragma unroll
  for (int e = 0; e < E; e++) { R[2 * e] = lds32(ta - e * 32); R[2 * e + 1] = lds32(ta - e * 32 - 16); }
}

__global__ void __launch_bounds__(512, 1)
fused_kernel(const __grid_constant__ CUtensorMap tm_x, const __grid_constant__ CUtensorMap tm_w,
             const __grid_constant__ CUtensorMap tm_wo,
             const __grid_constant__ CUtensorMap tm_out, const __grid_constant__ CUtensorMap tm_os,
             const __grid_constant__ CUtensorMap tm_ol, const __grid_constant__ CUtensorMap tm_xs,
             const __grid_constant__ CUtensorMap tm_xl, const __nv_bfloat16* __restrict__ x,
             const __nv_bfloat16* __restrict__ wphi,
             const __nv_bfloat16* __restrict__ logAr, const __nv_bfloat16* __restrict__ Aim,
             const __nv_bfloat16* __restrict__ Cre, const __nv_bfloat16* __restrict__ Cim,
             const __nv_bfloat16* __restrict__ logdt, const __nv_bfloat16* __restrict__ Dskip,
             const __nv_bfloat16* __restrict__ gatew) {
  extern __shared__ __align__(1024) unsigned char smem[];
  const uint32_t sb = smem_u32(smem);
  const int tid = threadIdx.x, warp = __shfl_sync(0xffffffffu, tid >> 5, 0), lane = tid & 31;
  const int wgi = __shfl_sync(0xffffffffu, tid >> 7, 0);
  const int g = lane >> 2, t = lane & 3;
  const int mi = lane >> 3, l7 = lane & 7;
  const int bid = blockIdx.x;
  const int hg_in = bid & 3, rt = (bid >> 2) & 15, hgblk = bid >> 6;
  const int hg = hgblk * 4 + hg_in;

  const uint32_t bar_full = sb + OFF_BAR;
  const uint32_t bar_empty = sb + OFF_BAR + 32;
  const uint32_t bar_full2 = sb + OFF_BAR + 64;
  const uint32_t bar_empty2 = sb + OFF_BAR + 128;
  const uint32_t bar_y = sb + OFF_BAR + 152;
  const uint32_t bar_vfree = sb + OFF_BAR + 160;
  const uint32_t bar_qfree = sb + OFF_BAR + 168;
  const uint32_t bar_aux = sb + OFF_BAR + 176;
  const uint32_t bar_ssm = sb + OFF_BAR + 184;
  const uint32_t bar_kv = sb + OFF_BAR + 192;
  const uint32_t bar_u = sb + OFF_BAR + 200;
  const uint32_t bar_mdone = sb + OFF_BAR + 208;
  const uint32_t bar_s0 = sb + OFF_BAR + 216;
  const uint32_t bar_xfree = sb + OFF_BAR + 224;
  const uint32_t bar_gw = sb + OFF_BAR + 232;
  const uint32_t bar_kg = sb + OFF_BAR + 240;
  const uint32_t bar_cv = sb + OFF_BAR + 248;
  const uint32_t sm_epoch = sb + OFF_BAR + 256;

  PROBEW(0, 0);

  if (wgi == 3) asm volatile("setmaxnreg.dec.sync.aligned.u32 64;");
  const int kch = hg * 64 + rt * 4 + (warp & 3);
  unsigned short q[16], rdt = 0;
  if (wgi == 2) {
    rdt = ldg16_now(logdt + kch);
#pragma unroll
    for (int i = 0; i < 4; i++) {
      const int n = kch * 128 + 32 * i + lane;
      q[4 * i] = ldg16_now(logAr + n); q[4 * i + 1] = ldg16_now(Aim + n);
      q[4 * i + 2] = ldg16_now(Cre + n); q[4 * i + 3] = ldg16_now(Cim + n);
    }
  }
  if (tid == 128) {
#pragma unroll
    for (int i = 0; i < 4; i++) mbar_init(bar_full + 8 * i, 1);
    asm volatile("fence.mbarrier_init.release.cluster;" ::: "memory");
#pragma unroll 1
    for (int st = 0; st < 4; st++) {
      const int k0 = (4 * hgblk + ((st + hg_in + 1) & 3)) * 64;
      const uint32_t dst = sb + OFF_RING + st * STAGE_BYTES;
      mbar_expect_tx(bar_full + 8 * st, STAGE_BYTES);
      tma_load_2d(dst, &tm_x, k0, rt * 128, bar_full + 8 * st);
      tma_load_2d(dst + 2 * BLK, &tm_w, hg * 64, k0, bar_full + 8 * st);
      tma_load_2d(dst + 3 * BLK, &tm_w, 512 + hg * 64, k0, bar_full + 8 * st);
      tma_load_2d(dst + 4 * BLK, &tm_w, 1024 + hg * 64, k0, bar_full + 8 * st);
    }
  }
  if (tid == 160) {
    constexpr unsigned long long c0 = 0x1111111188881111ull, c1 = 0x4422881341884814ull;
#pragma unroll
    for (int i = 4; i < 32; i++) mbar_init(sb + OFF_BAR + 8 * i, (int)(((i < 16 ? c0 : c1) >> (4 * (i & 15))) & 15));
    asm volatile("fence.mbarrier_init.release.cluster;" ::: "memory");
  }
  __syncwarp();
  if (wgi == 2) {
    asm volatile("bar.arrive 0, 512;" ::: "memory");
    asm volatile("setmaxnreg.inc.sync.aligned.u32 160;");
    PROBEW(8, 46);
    const int w = warp - 8;
    const int ch = kch;
    const uint32_t park = sb + OFF_SSM + w * PARK;
    const uint32_t park2 = sb + 3 * BLK + w * PARK;
    const uint32_t tab = sb + OFF_TAB + w * 2048;
    const uint32_t ub = sb + OFF_U + w * UST + 512;
    const float dsk = bf_lo(__ldg((const unsigned short*)Dskip + ch));
    uint32_t W[56], R[64];
    float klast = 0.f, ka[5][4];
  auto kstore = [&](const uint32_t* V, uint32_t xb) {
    const uint32_t qa = xb + g * 512 + t * 16, ra = xb + 4096 + g * 256 + t * 8, sa = xb + 6144 + g * 128 + t * 4;
#pragma unroll
    for (int gg = 0; gg < 8; gg++) {
      sts128(qa + ((gg ^ (g & 1)) << 6), V[7 * gg], V[7 * gg + 1], V[7 * gg + 2], V[7 * gg + 3]);
      sts64(ra + ((gg ^ (g & 3)) << 5), V[7 * gg + 4], V[7 * gg + 5]);
      sts32(sa + ((gg ^ g) << 4), V[7 * gg + 6]);
    }
  };
    {
      uint32_t pa[4] = {0, 0, 0, 0}, pc[4] = {0, 0, 0, 0};
      float dt = 1.f;
#pragma unroll 1
      for (int u = -1; u < 4; u++) {
        if (u == 0) {
          PROBEW(8, 42);
#pragma unroll
          for (int i = 0; i < 4; i++) { pa[i] = q[4 * i] | ((uint32_t)q[4 * i + 1] << 16); pc[i] = q[4 * i + 2] | ((uint32_t)q[4 * i + 3] << 16); }
          dt = bf_round(expf(bf_lo(rdt)));
          PROBEW(8, 16);
        }
        if (u == 3) {
#pragma unroll
          for (int i = 0; i < 56; i++) R[i] = W[i];
        }
        const float fa = bf_lo(pa[0]), fi = bf_hi(pa[0]), fr = bf_lo(pc[0]), fc = bf_hi(pc[0]);
        pa[0] = pa[1]; pa[1] = pa[2]; pa[2] = pa[3]; pc[0] = pc[1]; pc[1] = pc[2]; pc[2] = pc[3];
        const float ar2 = -bf_round(expf(fa)) * dt * LOG2E;
        const float ang = fi * dt;
        const cplx C = {2.f * fr * dt, 2.f * fc * dt};
        const cplx w1 = cexp_p(ar2, ang, 1.f), W128 = cexp_p(ar2, ang, 128.f), m2b = cexp_p(ar2, ang, 244.f);
        const cplx E2 = csqr(w1), m2a = csqr(E2), m3a = csqr(m2a), E16 = csqr(m3a), m3b = cmul(m2b, m2a);
        const cplx W256 = csqr(W128), W512 = csqr(W256), W1024 = csqr(W512), W2048 = csqr(W1024);
        klast += C.re * W2048.re - C.im * W2048.im;
        cplx Al = {1.f, 0.f}, Be = C, S2 = cmul(C, W512), S3 = cmul(C, W1024);
#pragma unroll
        for (int gg = 0; gg < 8; gg++) {
          const cplx Ah = gg ? cmul(Al, W128) : W128, Bo = cmul(Be, w1), B1 = cmul(Be, W256);
          W[7 * gg] = pack2(Al.re, -Al.im); W[7 * gg + 1] = pack2(Ah.re, -Ah.im); W[7 * gg + 2] = pack2(Be.re, Be.im);
          W[7 * gg + 3] = pack2(Bo.re, Bo.im); W[7 * gg + 4] = pack2(B1.re, B1.im); W[7 * gg + 5] = pack2(S2.re, S2.im);
          W[7 * gg + 6] = pack2(S3.re, S3.im);
          if (gg < 7) {
            Al = gg ? cmul(Al, E16) : E16;
            Be = cmul(Be, E2);
            S2 = cmul(S2, gg == 3 ? m2b : m2a);
            S3 = cmul(S3, (gg & 1) ? m3b : m3a);
          }
        }
        if (u < 2) kstore(W, park + (u & 1) * 7168);
      }
    }
    PROBEW(8, 17);
    asm volatile("bar.sync 3, 160;" ::: "memory");
    mbar_wait(bar_mdone, 0);
    kstore(W, park2);
    kstore(R, park2 + 7168);
#pragma unroll
    for (int s = 0; s < 5; s++) { ka[s][0] = ka[s][1] = ka[s][2] = ka[s][3] = 0.f; }
    __syncwarp();
#pragma unroll 1
    for (int u = 0; u < 4; u++) {
      const uint32_t xb = (u < 2 ? park : park2) + (u & 1) * 7168;
#pragma unroll
      for (int km = 0; km < 8; km++) {
        lds128_r(&R[8 * km], xb + km * 512 + ((lane ^ ((km & 1) << 2)) << 4));
        const uint2 r2 = lds64(xb + 4096 + km * 256 + ((lane ^ ((km & 3) << 2)) << 3));
        R[8 * km + 4] = r2.x; R[8 * km + 5] = r2.y;
        R[8 * km + 6] = lds32(xb + 6144 + km * 128 + ((lane ^ (km << 2)) << 2));
      }
#pragma unroll
      for (int km = 0; km < 8; km++)
#pragma unroll
        for (int s = 0; s < 5; s++) mma16808(ka[s], R[8 * km], R[8 * km + 1], R[8 * km + 2 + s]);
    }
    __syncwarp();
    if (lane == 0) mbar_arrive(bar_kg);
#pragma unroll
    for (int o = 16; o > 0; o >>= 1) klast += __shfl_xor_sync(0xffffffffu, klast, o);
    PROBEW(8, 18);
    mbar_wait(bar_gw, 0);
    {
        const uint32_t kw = park + 11776;
        {
          const float k512 = __shfl_sync(0xffffffffu, ka[3][0], 0), k1024 = __shfl_sync(0xffffffffu, ka[4][0], 0);
          if (lane == 0) ka[0][0] += dsk;
          if (lane == 31) ka[2][3] -= k512;
          float plo = __shfl_up_sync(0xffffffffu, ka[1][1], 1), phi = __shfl_up_sync(0xffffffffu, ka[1][3], 1);
          float nlo = __shfl_down_sync(0xffffffffu, ka[2][0], 1), nhi = __shfl_down_sync(0xffffffffu, ka[2][2], 1);
          const float l31 = __shfl_sync(0xffffffffu, ka[1][1], 31), h31 = __shfl_sync(0xffffffffu, ka[1][3], 31);
          const float e0 = __shfl_sync(0xffffffffu, ka[2][2], 0);
          if (lane == 0) { plo = 0.f; phi = l31; }
          if (lane == 31) { nlo = e0; nhi = 0.f; }
          sts128(kw + 64 + lane * 16, pack2(ka[0][0], plo), pack2(ka[1][0], ka[0][0]), pack2(ka[0][1], ka[1][0]), pack2(ka[1][1], ka[0][1]));
          sts128(kw + 576 + lane * 16, pack2(ka[0][2], phi), pack2(ka[1][2], ka[0][2]), pack2(ka[0][3], ka[1][2]), pack2(ka[1][3], ka[0][3]));
          sts128(kw + 1088 + lane * 16, pack2(ka[2][0], lane ? ka[2][0] : h31), pack2(ka[2][0], ka[2][0]), pack2(ka[2][1], ka[2][0]), pack2(nlo, ka[2][1]));
          sts128(kw + 1600 + lane * 16, pack2(ka[2][2], ka[2][2]), pack2(ka[2][2], ka[2][2]), pack2(ka[2][3], ka[2][2]), pack2(nhi, ka[2][3]));
          sts32(kw + (lane < 16 ? lane * 4 : (512 + lane) * 4), 0u);
          const int dd = lane - 16;
          sts32(tab + lane * 4, pack2((dd == -4 || dd == -3) ? -k1024 : 0.f, (dd == -3 || dd == -2) ? -k1024 : 0.f));
          sts32(tab + 128 + lane * 4, pack2((dd == 12 || dd == 13) ? -k1024 : 0.f, (dd == 13 || dd == 14) ? -k1024 : 0.f));
          sts32(tab + 256 + lane * 4, pack2(dd >= 12 ? klast : 0.f, dd >= 13 ? klast : 0.f));
          const uint32_t tw = tab + 512;
#pragma unroll
          for (int s = 0; s < 2; s++) { sts32(tw + s * 512 + lane * 4, 0u); sts32(tw + s * 512 + 384 + lane * 4, 0u); }
          const int i2 = 32 + 2 * g + (t & 1) + 32 * (t >> 1);
          sts32(tw + i2 * 4, pack2(ka[3][1], ka[3][0]));
          sts32(tw + (i2 + 16) * 4, pack2(ka[3][3], ka[3][2]));
          const int i3 = 32 + g + 16 * t;
          sts32(tw + 512 + i3 * 4, pack2(ka[4][1], ka[4][0]));
          sts32(tw + 512 + (i3 + 8) * 4, pack2(ka[4][3], ka[4][2]));
        }
        PROBEW(8, 19);
        mbar_wait(bar_u, 0);
        __syncwarp();
        PROBEW(8, 20); PROBEW(9, 28); PROBEW(10, 29); PROBEW(11, 30);
#pragma unroll 1
        for (int it = 0; it < 4; it++) {
          uint4 cu[2], nx[2], pv[2];
#pragma unroll
          for (int j = 0; j < 2; j++) {
            const int ci = it * 32 + lane + 96 * j - 16;
            cu[j] = lds128(ub + uch(ci)); nx[j] = lds128(ub + uch(ci + 1)); pv[j] = lds128(ub + uch(ci - 1));
          }
#pragma unroll
          for (int j = 0; j < 2; j++) {
            const int li = it * 32 + lane + 96 * j;
            const uint4 c = cu[j], n = nx[j], v = pv[j];
            const uint32_t xm = xw(v.w, c.x), x0 = xw(c.x, c.y), x1 = xw(c.y, c.z), x2 = xw(c.z, c.w), x3 = xw(c.w, n.x), x4 = xw(n.x, n.y), x5 = xw(n.y, n.z);
            const uint32_t s0 = hadd2(hadd2(xm, x0), c.x), s1 = hadd2(hadd2(x0, x1), c.y), s2 = hadd2(hadd2(x1, x2), c.z), s3 = hadd2(hadd2(x2, x3), c.w);
            const bool lo = j ? li < 211 : it < 3, hi = j ? li < 147 : it < 3;
            sts128_if(lo, park + li * 16, s2, s3, hadd2(hadd2(x3, x4), n.x), hadd2(hadd2(x4, x5), n.y));
            const uint32_t f0 = hadd2(hadd2(v.w, c.y), s0), f1 = hadd2(hadd2(c.x, c.z), s1), f2 = hadd2(hadd2(c.y, c.w), s2), f3 = hadd2(hadd2(c.z, n.x), s3);
            sts128_if(lo, park + 3504 + li * 16, f0, f1, f2, f3);
            const uint32_t h0 = hadd2(hadd2(xw(v.z, v.w), x1), f0), h1 = hadd2(hadd2(xm, x2), f1), h2 = hadd2(hadd2(x0, x3), f2), h3 = hadd2(hadd2(x1, x4), f3);
            sts128_if(hi, park + 6912 + li * 16, h0, h1, h2, h3);
            sts128_if(hi, park + 9344 + li * 16, hadd2(hadd2(v.z, c.z), h0), hadd2(hadd2(v.w, c.w), h1), hadd2(hadd2(c.x, n.x), h2),
                      hadd2(hadd2(c.y, n.y), h3));
          }
        }
        PROBEW(8, 31);
        float acc[16][4];
#pragma unroll
        for (int T = 0; T < 16; T++) { acc[T][0] = acc[T][1] = acc[T][2] = acc[T][3] = 0.f; }
        {
          const int uc = 2 * (l7 + (lane >> 4) * 8) + (mi & 1);
          const uint32_t kaddr = kw + (16 + g - 2 * t) * 4, caddr = tab + (16 + g - 2 * t) * 4;
          int opq;
          asm volatile("mov.u32 %0, %%nsmid;" : "=r"(opq));
          uint32_t* S = &R[32];
#pragma unroll
          for (int j = 0; j < 5; j++) ldsm_r(&R[4 * j], ub + uch(uc - 14) + j * 512);
          lda(&S[16], caddr + 128);
          lda(&S[20], caddr + 256);
          lda(&S[24], kaddr + 2048);
          lda(&S[28], caddr);
#pragma unroll
          for (int T = 7; T < 16; T++) mma16816(acc[T], S[16], S[17], S[18], S[19], R[2 * T - 14], R[2 * T - 13]);
          mma16816(acc[15], S[20], S[21], S[22], S[23], R[0], R[1]);
#pragma unroll
          for (int j = 0; j < 8; j++) ldsm_r(&R[4 * j], ub + uch(uc) + j * 512);
#pragma unroll
          for (int j = 0; j < 4; j++) lda(&S[4 * j], kaddr + j * 512);
#pragma unroll
          for (int T = 4; T < 16; T++) mma16816(acc[T], S[24], S[25], S[26], S[27], R[2 * T - 8], R[2 * T - 7]);
#pragma unroll
          for (int T = 8; T < 16; T++) mma16816(acc[T], S[28], S[29], S[30], S[31], R[2 * T - 16], R[2 * T - 15]);
#pragma unroll 1
          for (int mp = 0; mp < 4; mp++) {
#pragma unroll
            for (int hb = 0; hb < 2; hb++) {
              const int ml = 2 * mp + hb;
              uint32_t* Sc = &S[16 * hb];
              uint32_t* Sn = &S[16 - 16 * hb];
              const uint32_t kp = kaddr + ml * 64 + 64;
              const uint32_t uo = ub + uch(uc - 2 * ml), un = ub + uch(uc - 2 * ml - 2);
              if (opq > 2 * hb) {
                if (hb || true) {
#pragma unroll
                  for (int j = 4; j < 8; j++) ldsm_r(&R[4 * j], uo + j * 512);
                }
#pragma unroll
                for (int j = 0; j < 4; j++) lda(&Sn[4 * j], kp + j * 512);
#pragma unroll
                for (int m = 0; m < 4; m++)
#pragma unroll
                  for (int T = m; T < 8; T++) mma16816(acc[T], Sc[4 * m], Sc[4 * m + 1], Sc[4 * m + 2], Sc[4 * m + 3], R[2 * (T - m)], R[2 * (T - m) + 1]);
              }
              if (opq > 2 * hb + 1) {
                ldsm_r(&R[0], un);
                ldsm_r(&R[4], un + 512);
#pragma unroll
                for (int m = 3; m >= 0; m--) {
#pragma unroll
                  for (int T = 8; T < 16; T++) mma16816(acc[T], Sc[4 * m], Sc[4 * m + 1], Sc[4 * m + 2], Sc[4 * m + 3], R[2 * (T - m)], R[2 * (T - m) + 1]);
                  if (m == 3) ldsm_r(&R[8], un + 2 * 512);
                  if (m == 1) ldsm_r(&R[12], un + 3 * 512);
                }
              }
            }
          }
        }
        __syncwarp();
        if (lane == 0) mbar_arrive(bar_cv);
        PROBEW(8, 21); PROBEW(9, 25); PROBEW(10, 26); PROBEW(11, 27);
        const int c2 = l7 + 8 * (mi >> 1);
        const int r16 = (mi & 1) * 16;
        load_taps<10>(R, tab + 512 + (2 * g + 95 - t) * 4);
        __syncwarp();
        conv_seg<2, 10, -1, 23>(acc, R, park + ((c2 & 1) ? 3504 + ((c2 + 1) >> 1) * 16 : (c2 >> 1) * 16) + 128 + r16);
        PROBEW(8, 22);
        load_taps<9>(R, tab + 1024 + (g + 95 - t) * 4);
        conv_seg<3, 9, -1, 7>(acc, R, park + ((c2 & 1) ? 9344 : 6912) + (1 + c2) * 16 + r16);
        __syncwarp();
        if (lane == 0) mbar_arrive(bar_ssm);
        PROBEW(8, 23);
        {
          const uint32_t ya = park + ((lane >> 4) * 128 + l7 * 16 + (mi & 1) * 8) * 2;
          const uint32_t tag = g == 0 ? 0x00010001u : 0u;
#pragma unroll
          for (int T = 0; T < 16; T += 2)
            stsm_x4_t(ya + T * 256, pack2(acc[T][0], acc[T][1]) | tag, pack2(acc[T][2], acc[T][3]) | tag,
                      pack2(acc[T + 1][0], acc[T + 1][1]) | tag, pack2(acc[T + 1][2], acc[T + 1][3]) | tag);
          mbar_wait(bar_empty2 + 8, 0);
          __syncwarp();
#pragma unroll
          for (int i = 0; i < 8; i++) lds128_r(&R[4 * i], park + (i * 32 + lane) * 16);
#pragma unroll
          for (int i = 7; i >= 0; i--)
            st_relaxed_v4((uint4*)(g_yT + (size_t)ch * SEQ) + i * 32 + lane, R[4 * i], R[4 * i + 1], R[4 * i + 2], R[4 * i + 3]);
          PROBEW(8, 33);
          uint4* src = (uint4*)(g_yT + (size_t)(hg_in * 128 + w * 32 + mi) * SEQ + rt * 128 + hgblk * 64) + l7;
          uint4 v[8];
#pragma unroll
          for (int i = 0; i < 8; i++) v[i].x = 0;
          __nanosleep(YS0);
#pragma unroll 1
          for (int it = 0; it < SPIN_LIMIT; it++) {
            uint32_t mn = 0xffffffffu;
#pragma unroll
            for (int i = 0; i < 8; i++)
              if (v[i].x == 0) v[i] = ld_relaxed_v4(src + i * (4 * SEQ / 8));
#pragma unroll
            for (int i = 0; i < 8; i++) mn = min(mn, v[i].x);
            if (mn != 0) break;
          }
          __syncwarp();
          mbar_wait(bar_empty2, 0);
#pragma unroll
          for (int i = 0; i < 8; i++) {
            const int c = w * 32 + i * 4 + mi;
            sts128(sb + 14 * BLK + c * 128 + ((l7 ^ (c & 7)) << 4), v[i].x, v[i].y, v[i].z, v[i].w);
          }
          __syncwarp();
          if (lane == 0) {
            mbar_arrive(bar_y);
          }
        }
    }
    PROBEW(8, 24);
  } else if (wgi == 3) {
    if (warp == 12) asm volatile("bar.sync 0, 512;" ::: "memory");
    if (warp == 12) {
#pragma unroll 1
      for (int st = 0; st < 4; st++) {
        mbar_wait(bar_empty + 8 * st, 0);
        if (st == 3) mbar_wait(bar_xfree, 0);
        const int k0 = (4 + st - 4 * hgblk) * 64;
        const uint32_t dst = sb + OFF_RING + st * STAGE_BYTES;
        if (lane == 0) mbar_expect_tx(bar_full + 8 * st, STAGE_BYTES);
        __syncwarp();
        if (lane == 0) tma_load_2d(dst, &tm_x, k0, rt * 128, bar_full + 8 * st);
        else if (lane < 4) tma_load_2d(dst + (1 + lane) * BLK, &tm_w, (lane - 1) * 512 + hg * 64, k0, bar_full + 8 * st);
        __syncwarp();
      }
      PROBE(32);
      mbar_wait(bar_aux, 0);
      {
        const unsigned target = (lds32(sm_epoch) & ~127u) + 128u;
        const uint32_t bar = bar_full2 + 8 * (lane & 7);
        const uint32_t wbar = lane < 3 ? bar_vfree : lane < 6 ? bar_kg : bar_ssm;
        const uint32_t obar = lane < 2 ? bar_mdone : lane < 5 ? bar_qfree : bar_cv;
        const int cch = (lane + 4 * hgblk) & 7;
        const unsigned* flag = &g_ocnt[(rt * 2 + hgblk) * 8 + cch];
        bool need_w = lane < 8, need_o = lane < 8;
        if (lane < 8) mbar_expect_tx(bar, 3 * BLK);
#pragma unroll 1
        for (int it = 0; it < (SPIN_LIMIT << 3); it++) {
          if (need_w && mbar_test(wbar, 0)) {
            tma_load_2d(sb + w_off(lane, 0), &tm_wo, hg_in * 128, cch * 64, bar);
            tma_load_2d(sb + w_off(lane, 1), &tm_wo, hg_in * 128 + 64, cch * 64, bar);
            need_w = false;
          }
          if (need_o && mbar_test(obar, 0) && (int)(ld_relaxed(flag) - target) >= 0) {
            (void)ld_acquire(flag);
            fence_async_global();
            tma_load_2d(sb + o_off(lane), &tm_ol, cch * 64, rt * 128 + hgblk * 64, bar);
            need_o = false;
          }
          if (!__any_sync(0xffffffffu, need_w || need_o)) break;
          __nanosleep(40);
        }
        if (lane == 0) red_add(&g_done, 1u);
      }
    } else {
      if (warp == 14) {
        const unsigned done = ld_relaxed(&g_done);
        asm volatile("bar.sync 0, 512;" ::: "memory");
        uint32_t w4[16];
#pragma unroll
        for (int i = 0; i < 16; i++) {
          const unsigned short* wb = (const unsigned short*)wphi + (hg * 4 + (i >> 2)) * 256 + 2 * t * 16 + g + (i & 1) * 128 + ((i >> 1) & 1) * 8;
          w4[i] = (uint32_t)__ldg(wb) | ((uint32_t)__ldg(wb + 16) << 16);
        }
#pragma unroll
        for (int h = 0; h < 4; h++) sts128(sb + OFF_WPHI + h * 512 + lane * 16, w4[4 * h], w4[4 * h + 1], w4[4 * h + 2], w4[4 * h + 3]);
        if (lane == 0) sts32(sm_epoch, done);
        __syncwarp();
        if (lane == 0) mbar_arrive(bar_aux);
        mbar_wait(bar_s0, 0);
#pragma unroll
        for (int i = 0; i < 4; i++) sts128(sb + OFF_U + i * UST + lane * 16, 0, 0, 0, 0);
        __syncwarp();
        if (lane == 0) {
          wait_cnt(&g_xcnt[hg * 32], (done & ~127u) + 128u);
          fence_async_global();
          mbar_expect_tx(bar_u, 16384);
#pragma unroll 1
          for (int i = 0; i < 4; i++) tma_load_2d(sb + OFF_U + i * UST + 512, &tm_xl, 0, (hg * 64 + rt * 4 + i) * 128, bar_u);
          PROBE(35);
        }
        __syncwarp();
      } else {
        const int half = (warp - 13) >> 1;
        const int row0 = rt * 128 + hg * 16 + half * 8;
        const uint4* xr = (const uint4*)(x + (size_t)row0 * DM) + lane;
        float mine = 0.f;
        if (lane < 24) g_kva[hg * 768 + rt * 48 + half * 24 + lane] = make_float4(0.f, 0.f, 0.f, 0.f);
        asm volatile("bar.sync 0, 512;" ::: "memory");
        {
            mbar_wait(bar_full + 24, 0);
            const uint32_t stg = sb + OFF_TAB + half * 4096;
#pragma unroll 1
            for (int rd = 0; rd < 2; rd++) {
              const uint32_t src = sb + OFF_RING + 3 * STAGE_BYTES + (64 * half + 32 * rd + lane) * 128;
              uint32_t r[8][4];
#pragma unroll
              for (int cc = 0; cc < 8; cc++) ldsm_x4(r[cc][0], r[cc][1], r[cc][2], r[cc][3], src + ((cc ^ l7) << 4));
              if (rd == 1) {
                if (lane == 0) asm volatile("cp.async.bulk.wait_group.read 0;" ::: "memory");
                __syncwarp();
              }
#pragma unroll
              for (int cc = 0; cc < 8; cc++) stsm_x4_t(stg + (cc * 8 + l7) * 64 + ((mi ^ ((l7 >> 1) & 3)) << 4), r[cc][0], r[cc][1], r[cc][2], r[cc][3]);
              asm volatile("fence.proxy.async.shared::cta;" ::: "memory");
              __syncwarp();
              if (lane == 0) tma_store_2d(&tm_xs, stg, rt * 128 + 64 * half + 32 * rd, hg * 64);
            }
            if (lane == 0) mbar_arrive(bar_xfree);
            PROBEW(13, 47);
            __threadfence();
            __syncwarp();
            if (lane == 0) {
              asm volatile("cp.async.bulk.wait_group 0;" ::: "memory");
              mbar_arrive(bar_gw);
              red_add(&g_xcnt[hg * 32], 4u);
            }
            PROBEW(13, 37);
          }
#pragma unroll 1
        for (int b = 0; b < NGB; b++) {
          const uint4 gw = __ldg((const uint4*)gatew + b * 32 + lane);
          uint4 a[8];
#pragma unroll
          for (int r = 0; r < 8; r++) a[r] = __ldg(xr + r * 64 + b * 32);
          float sr[8];
#pragma unroll
          for (int r = 0; r < 8; r++) {
            float s = bf_lo(a[r].x) * bf_lo(gw.x);
            s = fmaf(bf_hi(a[r].x), bf_hi(gw.x), s); s = fmaf(bf_lo(a[r].y), bf_lo(gw.y), s); s = fmaf(bf_hi(a[r].y), bf_hi(gw.y), s);
            s = fmaf(bf_lo(a[r].z), bf_lo(gw.z), s); s = fmaf(bf_hi(a[r].z), bf_hi(gw.z), s);
            s = fmaf(bf_lo(a[r].w), bf_lo(gw.w), s); sr[r] = fmaf(bf_hi(a[r].w), bf_hi(gw.w), s);
          }
#pragma unroll
          for (int i = 0; i < 4; i++) sr[i] = ((lane & 16) ? sr[i + 4] : sr[i]) + __shfl_xor_sync(0xffffffffu, (lane & 16) ? sr[i] : sr[i + 4], 16);
#pragma unroll
          for (int i = 0; i < 2; i++) sr[i] = ((lane & 8) ? sr[i + 2] : sr[i]) + __shfl_xor_sync(0xffffffffu, (lane & 8) ? sr[i] : sr[i + 2], 8);
          mine += ((lane & 4) ? sr[1] : sr[0]) + __shfl_xor_sync(0xffffffffu, (lane & 4) ? sr[0] : sr[1], 4);
        }
        mine += __shfl_xor_sync(0xffffffffu, mine, 1);
        mine += __shfl_xor_sync(0xffffffffu, mine, 2);
        if (t == 0) g_gate[row0 + g] = 1.f / (1.f + __expf(-mine));
        {
          uint4* yz = (uint4*)(g_yT + (size_t)(hg_in * 128 + half * 64 + mi) * SEQ + rt * 128 + hgblk * 64) + l7;
#pragma unroll 4
          for (int i = 0; i < 16; i++) yz[i * (4 * SEQ / 8)] = make_uint4(0, 0, 0, 0);
        }
        __threadfence();
        __syncwarp();
        if (lane == 0) red_add(&g_xcnt[(8 + half) * 32], 1u);
        PROBEW(13, 38);
      }
      const int idx = (warp - 13) * 32 + lane;
      mbar_wait(bar_vfree, 0);
      {
        const float4* src = g_kva + hg * 768 + idx;
        const bool three = idx < 64;
        uint4 v[9];
#pragma unroll 1
        for (int it = 0; it < SPIN_LIMIT; it++) {
          bool ok = true;
#pragma unroll
          for (int i = 0; i < 9; i++)
            if (i < 6 || three) v[i] = ld_relaxed_v4(src + (i / 3) * 96 + (i % 3) * 256);
#pragma unroll
          for (int i = 0; i < 9; i++)
            if (i < 6 || three) ok = ok && v[i].w == 0x41800000u;
          if (ok) break;
          __nanosleep(100);
        }
        mbar_wait(bar_kg, 0);
#pragma unroll
        for (int r = 0; r < 3; r++) {
          if (r < 2 || three) {
            const int i = idx + 96 * r;
            const uint4 a = v[3 * r], b = v[3 * r + 1], c = v[3 * r + 2];
            sts128(sb + OFF_KV + i * 16, pack2(__uint_as_float(a.x), __uint_as_float(a.y)), pack2(__uint_as_float(a.z), __uint_as_float(b.x)),
                   pack2(__uint_as_float(b.y), __uint_as_float(b.z)), pack2(__uint_as_float(c.x), __uint_as_float(c.y)));
            if (g < 4) sts16(sb + OFF_KV + 4096 + (i >> 5) * 32 + t * 8 + g * 2, (uint16_t)pack2(__uint_as_float(c.z), 0.f));
          }
        }
        __syncwarp();
        if (lane == 0) mbar_arrive(bar_kv);
      }
      PROBEW(13, 36);
      if (tid == 448) {
        const unsigned target = (lds32(sm_epoch) & ~127u) + 128u;
        wait_cnt(&g_xcnt[8 * 32], target);
        wait_cnt(&g_xcnt[9 * 32], target);
        mbar_arrive(bar_empty2 + 8);
      }
    }
  } else {
    if (warp == 5) asm volatile("bar.arrive 3, 160;" ::: "memory");
    asm volatile("bar.sync 0, 512;" ::: "memory");
    asm volatile("setmaxnreg.inc.sync.aligned.u32 144;");
    const int wg = wgi, wq = warp & 3;
    const int srow = warp * 16 + l7 + (mi & 1) * 8;
    const int hi16 = lane >> 4;
    const uint32_t ONE = 0x3F803F80u;
    uint32_t kq[8][4];
    {
      float d[96];
#pragma unroll 1
      for (int kc = 0; kc < 8; kc++) {
        const int st = kc & 3;
        mbar_wait(bar_full + 8 * st, kc >> 2);
        if (kc == 0) PROBEW(0, 1);
        const uint32_t sa = sb + OFF_RING + st * STAGE_BYTES + wg * BLK;
        const uint32_t sw = sb + OFF_RING + st * STAGE_BYTES + 2 * BLK;
        wg_fence();
#pragma unroll
        for (int k = 0; k < 4; k++)
          wgmma_ss_n192(d, make_desc(sa + k * 32, 16, 1024), make_desc(sw + k * 2048, BLK, 1024), (kc | k) != 0);
        wg_commit();
        if (kc > 0) {
          wg_wait<1>();
          if (lane == 0) {
            mbar_arrive(bar_empty + 8 * ((kc - 1) & 3));
            if (kc == 5) mbar_arrive(bar_s0);
          }
        }
      }
      wg_wait<0>();
      if (lane == 0) mbar_arrive(bar_mdone);
      PROBEW(0, 2);
#pragma unroll
      for (int h = 0; h < 4; h++)
#pragma unroll
        for (int i = 0; i < 4; i++) {
          kq[h][i] = pack2(d[32 + 8 * h + 2 * i], d[33 + 8 * h + 2 * i]);
          kq[4 + h][i] = pack2(d[8 * h + 2 * i], d[8 * h + 2 * i + 1]);
        }
      mbar_wait(bar_mdone, 0);
#pragma unroll
      for (int h = 0; h < 4; h++) {
        const int jv = 64 + 8 * h;
        stsm_x4(sb + OFF_VST + srow * 128 + (((2 * h + hi16) ^ l7) << 4), pack2(d[jv], d[jv + 1]), pack2(d[jv + 2], d[jv + 3]),
                pack2(d[jv + 4], d[jv + 5]), pack2(d[jv + 6], d[jv + 7]));
      }
    }
    mbar_wait(bar_aux, 0);
#pragma unroll 1
    for (int it = 0; it < 2; it++) {
      PROBEW(0, 40 + it);
      float ep[4][2][4], en[4][2][4];
      uint32_t lg[4][4];
      float pmin = 1.f;
      {
        uint4 wp[4];
        float c0[4][4], c1[4][4];
#pragma unroll
        for (int j = 0; j < 4; j++) wp[j] = lds128(sb + OFF_WPHI + j * 512 + lane * 16);
#pragma unroll
        for (int j = 0; j < 4; j++) {
#pragma unroll
          for (int i = 0; i < 4; i++) { c0[j][i] = 0.f; c1[j][i] = 0.f; }
          mma16816(c0[j], kq[j][0], kq[j][1], kq[j][2], kq[j][3], wp[j].x, wp[j].y);
          mma16816(c1[j], kq[j][0], kq[j][1], kq[j][2], kq[j][3], wp[j].z, wp[j].w);
        }
#pragma unroll
        for (int j = 0; j < 4; j++) {
          lg[j][0] = pack2(c0[j][0], c0[j][1]); lg[j][1] = pack2(c1[j][0], c1[j][1]);
          lg[j][2] = pack2(c0[j][2], c0[j][3]); lg[j][3] = pack2(c1[j][2], c1[j][3]);
        }
      }
#pragma unroll
      for (int j = 0; j < 4; j++) {
        const uint32_t ma = hmax2(lg[j][0], lg[j][1]), mb = hmax2(lg[j][2], lg[j][3]);
        uint32_t m = hmax2(__byte_perm(ma, mb, 0x5410), __byte_perm(ma, mb, 0x7632));
        m = hmax2(m, __shfl_xor_sync(0xffffffffu, m, 1));
        m = hmax2(m, __shfl_xor_sync(0xffffffffu, m, 2));
#pragma unroll
        for (int r = 0; r < 2; r++) {
          const float ml = -(r ? bf_hi(m) : bf_lo(m)) * LOG2E;
          float* e = ep[j][r];
          e[0] = ex2f(fmaf(bf_lo(lg[j][2 * r]), LOG2E, ml)); e[1] = ex2f(fmaf(bf_hi(lg[j][2 * r]), LOG2E, ml));
          e[2] = ex2f(fmaf(bf_lo(lg[j][2 * r + 1]), LOG2E, ml)); e[3] = ex2f(fmaf(bf_hi(lg[j][2 * r + 1]), LOG2E, ml));
          const float s01 = e[0] * e[1], s23 = e[2] * e[3], pr = s01 * s23, rr = rcpf(pr);
          const float i01 = rr * s23, i23 = rr * s01;
          en[j][r][0] = i01 * e[1]; en[j][r][1] = i01 * e[0]; en[j][r][2] = i23 * e[3]; en[j][r][3] = i23 * e[2];
          pmin = fminf(pmin, pr);
        }
      }
      if (__any_sync(0xffffffffu, !(pmin >= 7.9e-31f))) {
#pragma unroll
        for (int j = 0; j < 4; j++) {
          const uint32_t ma = hmin2(lg[j][0], lg[j][1]), mb = hmin2(lg[j][2], lg[j][3]);
          uint32_t m = hmin2(__byte_perm(ma, mb, 0x5410), __byte_perm(ma, mb, 0x7632));
          m = hmin2(m, __shfl_xor_sync(0xffffffffu, m, 1));
          m = hmin2(m, __shfl_xor_sync(0xffffffffu, m, 2));
#pragma unroll
          for (int r = 0; r < 2; r++) {
            const float ml = (r ? bf_hi(m) : bf_lo(m)) * LOG2E;
            en[j][r][0] = ex2f(fmaf(bf_lo(lg[j][2 * r]), -LOG2E, ml)); en[j][r][1] = ex2f(fmaf(bf_hi(lg[j][2 * r]), -LOG2E, ml));
            en[j][r][2] = ex2f(fmaf(bf_lo(lg[j][2 * r + 1]), -LOG2E, ml)); en[j][r][3] = ex2f(fmaf(bf_hi(lg[j][2 * r + 1]), -LOG2E, ml));
          }
        }
      }
      const uint32_t prow = sb + OFF_PHK + srow * 256;
      uint32_t Pk[4][4], Nk[4][4];
#pragma unroll
      for (int j = 0; j < 4; j++) {
        Pk[j][0] = pack2(ep[j][0][0], ep[j][0][1]); Pk[j][1] = pack2(ep[j][1][0], ep[j][1][1]);
        Pk[j][2] = pack2(ep[j][0][2], ep[j][0][3]); Pk[j][3] = pack2(ep[j][1][2], ep[j][1][3]);
        Nk[j][0] = pack2(en[j][0][0], en[j][0][1]); Nk[j][1] = pack2(en[j][1][0], en[j][1][1]);
        Nk[j][2] = pack2(en[j][0][2], en[j][0][3]); Nk[j][3] = pack2(en[j][1][2], en[j][1][3]);
      }
      if (it == 0) {
        float spa[4][4], sna[4][4];
#pragma unroll
        for (int j = 0; j < 4; j++) {
#pragma unroll
          for (int i = 0; i < 4; i++) { spa[j][i] = 0.f; sna[j][i] = 0.f; }
          mma16816(spa[j], Pk[j][0], Pk[j][1], Pk[j][2], Pk[j][3], ONE, ONE);
          mma16816(sna[j], Nk[j][0], Nk[j][1], Nk[j][2], Nk[j][3], ONE, ONE);
        }
#pragma unroll
        for (int j = 0; j < 4; j++) {
          const float r0 = rcpf(spa[j][0] * sna[j][0]), r1 = rcpf(spa[j][2] * sna[j][2]);
          const float p0 = r0 * sna[j][0], n0 = r0 * spa[j][0], p1 = r1 * sna[j][2], n1 = r1 * spa[j][2];
          Pk[j][0] = pack2(ep[j][0][0] * p0, ep[j][0][1] * p0); Pk[j][1] = pack2(ep[j][1][0] * p1, ep[j][1][1] * p1);
          Pk[j][2] = pack2(ep[j][0][2] * p0, ep[j][0][3] * p0); Pk[j][3] = pack2(ep[j][1][2] * p1, ep[j][1][3] * p1);
          Nk[j][0] = pack2(en[j][0][0] * n0, en[j][0][1] * n0); Nk[j][1] = pack2(en[j][1][0] * n1, en[j][1][1] * n1);
          Nk[j][2] = pack2(en[j][0][2] * n0, en[j][0][3] * n0); Nk[j][3] = pack2(en[j][1][2] * n1, en[j][1][3] * n1);
          stsm_x4(prow + (((4 * j + hi16) ^ l7) << 4), Pk[j][0], Pk[j][1], Pk[j][2], Pk[j][3]);
          stsm_x4(prow + (((4 * j + 2 + hi16) ^ l7) << 4), Nk[j][0], Nk[j][1], Nk[j][2], Nk[j][3]);
        }
#pragma unroll
        for (int i = 0; i < 16; i++) kq[i >> 2][i & 3] = kq[(i >> 2) + 4][i & 3];
      } else {
#pragma unroll
        for (int i = 0; i < 16; i++) { kq[i >> 2][i & 3] = Pk[i >> 2][i & 3]; kq[4 + (i >> 2)][i & 3] = Nk[i >> 2][i & 3]; }
      }
      PROBEW(0, 44 + it);
      if (it == 0) {
        named_bar(1, 256);
        PROBEW(0, 3);
        const int hh = warp >> 1, ks = warp & 1;
        float D[2][4][4];
#pragma unroll
        for (int i = 0; i < 8; i++) { D[i >> 2][i & 3][0] = D[i >> 2][i & 3][1] = D[i >> 2][i & 3][2] = D[i >> 2][i & 3][3] = 0.f; }
        const uint32_t va = sb + OFF_VST + (l7 + (mi >> 1) * 8) * 128 + (((2 * hh + (mi & 1)) ^ l7) << 4);
        const uint32_t pa = sb + OFF_PHK + (l7 + (mi & 1) * 8) * 256 + (((4 * hh + 2 * ks + (mi >> 1)) ^ l7) << 4);
        uint32_t A[8][4], B[8][4];
#pragma unroll
        for (int s = 0; s < 8; s++) {
          ldsm_x4_t(A[s][0], A[s][1], A[s][2], A[s][3], va + s * 16 * 128);
          ldsm_x4_t(B[s][0], B[s][1], B[s][2], B[s][3], pa + s * 16 * 256);
        }
#pragma unroll
        for (int s = 0; s < 8; s++) {
          mma16816(D[s & 1][0], A[s][0], A[s][1], A[s][2], A[s][3], B[s][0], B[s][1]);
          mma16816(D[s & 1][1], A[s][0], A[s][1], A[s][2], A[s][3], B[s][2], B[s][3]);
          mma16816(D[s & 1][2], ONE, ONE, ONE, ONE, B[s][0], B[s][1]);
          mma16816(D[s & 1][3], ONE, ONE, ONE, ONE, B[s][2], B[s][3]);
        }
        const float zz = (g & 2) ? ((g & 1) ? D[0][3][1] + D[1][3][1] : D[0][3][0] + D[1][3][0])
                                 : ((g & 1) ? D[0][2][1] + D[1][2][1] : D[0][2][0] + D[1][2][0]);
        float4* kp = g_kva + hg * 768 + tid;
        mbar_wait(bar_u, 0);
        red_v4(kp, D[0][0][0] + D[1][0][0], D[0][0][1] + D[1][0][1], D[0][1][0] + D[1][1][0]);
        red_v4(kp + 256, D[0][1][1] + D[1][1][1], D[0][0][2] + D[1][0][2], D[0][0][3] + D[1][0][3]);
        red_v4(kp + 512, D[0][1][2] + D[1][1][2], D[0][1][3] + D[1][1][3], zz);
        __syncwarp();
        if (lane == 0) mbar_arrive(bar_vfree);
        PROBEW(0, 4);
      }
    }
    PROBEW(0, 5);
    const int row0 = rt * 128 + hgblk * 64 + wq * 16 + g;
    uint32_t gv0 = 0, gv1 = 0;
    const uint32_t os = sb + OFF_PHQ + warp * 2048;
    {
      uint32_t ow[4][4];
      mbar_wait(bar_kv, 0);
      PROBEW(0, 6);
      uint4 kP[4], kN[4];
      uint2 zP[4], zN[4];
#pragma unroll
      for (int h = 0; h < 4; h++) {
        zP[h] = lds64(sb + OFF_KV + 4096 + h * 64 + t * 8); zN[h] = lds64(sb + OFF_KV + 4096 + h * 64 + 32 + t * 8);
        kP[h] = lds128(sb + OFF_KV + h * 1024 + lane * 16);
        kN[h] = lds128(sb + OFF_KV + h * 1024 + 512 + lane * 16);
      }
#pragma unroll
      for (int h = 0; h < 4; h++) {
        float P0[4] = {0.f, 0.f, 0.f, 0.f}, P1[4] = {0.f, 0.f, 0.f, 0.f}, PZ[4] = {0.f, 0.f, 0.f, 0.f};
        float N0[4] = {0.f, 0.f, 0.f, 0.f}, N1[4] = {0.f, 0.f, 0.f, 0.f}, NZ[4] = {0.f, 0.f, 0.f, 0.f};
        mma16816(PZ, kq[h][0], kq[h][1], kq[h][2], kq[h][3], (g & 1) ? ONE : zP[h].x, (g & 1) ? ONE : zP[h].y);
        mma16816(NZ, kq[4 + h][0], kq[4 + h][1], kq[4 + h][2], kq[4 + h][3], (g & 1) ? ONE : zN[h].x, (g & 1) ? ONE : zN[h].y);
        mma16816(P0, kq[h][0], kq[h][1], kq[h][2], kq[h][3], kP[h].x, kP[h].y);
        mma16816(P1, kq[h][0], kq[h][1], kq[h][2], kq[h][3], kP[h].z, kP[h].w);
        mma16816(N0, kq[4 + h][0], kq[4 + h][1], kq[4 + h][2], kq[4 + h][3], kN[h].x, kN[h].y);
        mma16816(N1, kq[4 + h][0], kq[4 + h][1], kq[4 + h][2], kq[4 + h][3], kN[h].z, kN[h].w);
#pragma unroll
        for (int r = 0; r < 2; r++) {
          const float rn = rcpf(NZ[2 * r + 1]), sp = PZ[2 * r + 1] * rn;
          const float id = rcpf(fmaf(NZ[2 * r], sp, fmaf(1e-6f, PZ[2 * r + 1], PZ[2 * r])));
          const float fN = sp * id;
          ow[h][r] = pack2(fmaf(P0[2 * r], id, N0[2 * r] * fN), fmaf(P0[2 * r + 1], id, N0[2 * r + 1] * fN));
          ow[h][2 + r] = pack2(fmaf(P1[2 * r], id, N1[2 * r] * fN), fmaf(P1[2 * r + 1], id, N1[2 * r + 1] * fN));
        }
      }
#pragma unroll
      for (int h = 0; h < 4; h++)
        stsm_x4(os + (l7 + (mi & 1) * 8) * 128 + (((2 * h + hi16) ^ l7) << 4), ow[h][0], ow[h][1], ow[h][2], ow[h][3]);
      asm volatile("fence.proxy.async.shared::cta;" ::: "memory");
      __syncwarp();
      PROBEW(0, 10);
      if (lane == 0) {
        tma_store_2d(&tm_os, os, hg * 64, rt * 128 + warp * 16);
        asm volatile("cp.async.bulk.wait_group 0;" ::: "memory");
        if (wg == 0) mbar_arrive(bar_qfree);
        PROBEW(0, 13);
        fence_async_global();
        red_add(&g_ocnt[(rt * 2 + wg) * 8 + hg], 32u);
      }
      __syncwarp();
    }
    PROBEW(0, 7);
    {
    float acc[64];
    if (wg == 0) mbar_wait(bar_ssm, 0);
#pragma unroll 1
    for (int i = 8 * wg; i < 8; i++) {
      mbar_wait(bar_full2 + 8 * i, 0);
      PROBEW(1, 48 + i);
      if (i == 0) PROBEW(0, 8);
      if (i == 3) { gv0 = ld_relaxed(&g_gate[row0]); gv1 = ld_relaxed(&g_gate[row0 + 8]); }
      const uint32_t sa = sb + o_off(i), sw = sb + w_off(i, 0), lbo = i < 6 ? BLK : PARK;
      wg_fence();
#pragma unroll
      for (int k = 0; k < 4; k++) wgmma_ss_n128(acc, make_desc(sa + k * 32, 16, 1024), make_desc(sw + k * 2048, lbo, 1024), (i | k) != 0);
      wg_commit();
      if (i > 0) {
        wg_wait<1>();
        if (i == 1 && lane == 0) mbar_arrive(bar_empty2);
      }
    }
    if (wg == 0) mbar_wait(bar_y, 0);
    PROBEW(0, 11);
    {
      const float g0 = __uint_as_float(gv0), g1 = __uint_as_float(gv1);
      const float h0 = 1.f - g0, h1 = 1.f - g1;
      const uint32_t ya = sb + 14 * BLK + ((mi >> 1) * 8 + l7) * 128 + (((2 * wq + (mi & 1)) ^ l7) << 4);
      uint32_t y[8][4];
#pragma unroll
      for (int np = 0; np < 8; np++) ldsm_x4_t(y[np][0], y[np][1], y[np][2], y[np][3], ya + np * 16 * 128);
      wg_wait<0>();
      PROBEW(0, 9);
      const uint32_t ob = wg ? os : sb + 4 * BLK + wq * 2048;
      const uint32_t oa = ob + (l7 + (mi & 1) * 8) * 128;
#pragma unroll
      for (int np = 0; np < 8; np++) {
        const int j = np * 8;
        stsm_x4(oa + (wg ? 0 : (np >> 2) * BLK) + (((2 * (np & 3) + hi16) ^ l7) << 4),
                pack2(fmaf(g0, acc[j], h0 * bf_lo(y[np][0])), fmaf(g0, acc[j + 1], h0 * bf_hi(y[np][0]))),
                pack2(fmaf(g1, acc[j + 2], h1 * bf_lo(y[np][1])), fmaf(g1, acc[j + 3], h1 * bf_hi(y[np][1]))),
                pack2(fmaf(g0, acc[j + 4], h0 * bf_lo(y[np][2])), fmaf(g0, acc[j + 5], h0 * bf_hi(y[np][2]))),
                pack2(fmaf(g1, acc[j + 6], h1 * bf_lo(y[np][3])), fmaf(g1, acc[j + 7], h1 * bf_hi(y[np][3]))));
      }
      asm volatile("fence.proxy.async.shared::cta;" ::: "memory");
      __syncwarp();
      if (lane == 0 && wg == 1) mbar_arrive(bar_qfree);
      if (lane == 0 && wg == 0) {
        tma_store_2d(&tm_out, ob, hg_in * 128, rt * 128 + hgblk * 64 + wq * 16);
        tma_store_2d(&tm_out, ob + BLK, hg_in * 128 + 64, rt * 128 + hgblk * 64 + wq * 16);
        asm volatile("cp.async.bulk.wait_group.read 0;" ::: "memory");
      }
      PROBEW(0, 12);
    }
    }
  }
}

typedef CUresult (*EncodeFn)(CUtensorMap*, CUtensorMapDataType, cuuint32_t, void*, const cuuint64_t*, const cuuint64_t*,
                             const cuuint32_t*, const cuuint32_t*, CUtensorMapInterleave, CUtensorMapSwizzle,
                             CUtensorMapL2promotion, CUtensorMapFloatOOBfill);

void make_map(EncodeFn fn, CUtensorMap* m, const void* p, uint64_t cols, uint64_t rows, uint32_t bc, uint32_t br,
              CUtensorMapSwizzle sw = CU_TENSOR_MAP_SWIZZLE_128B) {
  cuuint64_t dims[2] = {cols, rows};
  cuuint64_t strides[1] = {cols * 2};
  cuuint32_t box[2] = {bc, br};
  cuuint32_t es[2] = {1, 1};
  fn(m, CU_TENSOR_MAP_DATA_TYPE_BFLOAT16, 2, const_cast<void*>(p), dims, strides, box, es, CU_TENSOR_MAP_INTERLEAVE_NONE,
     sw, CU_TENSOR_MAP_L2_PROMOTION_L2_256B, CU_TENSOR_MAP_FLOAT_OOB_FILL_NONE);
}

}

extern "C" void kernel_launch(void* const* d_in, const int* in_sizes, int n_in, void* d_out, int out_size) {
  (void)in_sizes; (void)n_in; (void)out_size;
  static EncodeFn fn = nullptr;
  static void* optr = nullptr;
  static void* xptr = nullptr;
  if (!fn) {
    void* p = nullptr;
    cudaDriverEntryPointQueryResult st;
    cudaGetDriverEntryPoint("cuTensorMapEncodeTiled", &p, cudaEnableDefault, &st);
    fn = (EncodeFn)p;
    cudaGetSymbolAddress(&optr, g_o);
    cudaGetSymbolAddress(&xptr, g_xT);
    cudaFuncSetAttribute(fused_kernel, cudaFuncAttributeMaxDynamicSharedMemorySize, SMEM_BYTES);
  }
  typedef const __nv_bfloat16* bp;
  CUtensorMap tx, tw, two, to, tos, tol, txs, txl;
  make_map(fn, &tx, d_in[0], 512, 2048, 64, 128);
  make_map(fn, &tw, d_in[1], 1536, 512, 64, 64);
  make_map(fn, &two, d_in[3], 512, 512, 64, 64);
  make_map(fn, &to, d_out, 512, 2048, 64, 16);
  make_map(fn, &tos, optr, 512, 2048, 64, 16);
  make_map(fn, &tol, optr, 512, 2048, 64, 64);
  make_map(fn, &txs, xptr, 2048, 512, 32, 64, CU_TENSOR_MAP_SWIZZLE_64B);
  make_map(fn, &txl, xptr, 16, 65536, 16, 128, CU_TENSOR_MAP_SWIZZLE_32B);
  fused_kernel<<<NCTA, 512, SMEM_BYTES, cudaStreamPerThread>>>(
      tx, tw, two, to, tos, tol, txs, txl, (bp)d_in[0], (bp)d_in[2], (bp)d_in[5], (bp)d_in[6], (bp)d_in[7], (bp)d_in[8], (bp)d_in[9],
      (bp)d_in[10], (bp)d_in[11]);
}
```

```cpp
#include <cuda_runtime.h>
#include <cuda_bf16.h>
#include <cuda.h>
#include <stdint.h>

#define DEVINL __device__ __forceinline__

namespace {

constexpr int SEQ = 2048;
constexpr int DM = 512;
constexpr int NCTA = 128;

__device__ float4 g_kva[8 * 768];
__device__ float g_gate[SEQ];
__device__ __align__(1024) __nv_bfloat16 g_o[SEQ * DM];
__device__ __align__(1024) __nv_bfloat16 g_yT[DM * SEQ];
__device__ __align__(1024) __nv_bfloat16 g_xT[DM * SEQ];
__device__ unsigned g_done;
__device__ unsigned g_xcnt[10 * 32];
__device__ unsigned g_ocnt[16 * 2 * 8];

constexpr int BLK = 8192;
constexpr int STAGE_BYTES = 5 * BLK;
constexpr int OFF_RING = 0;
constexpr int OFF_U = 0;
constexpr int UST = 4608;
constexpr int OFF_KV = 3 * BLK;
constexpr int OFF_PHQ = 10 * BLK;
constexpr int OFF_VST = 14 * BLK;
constexpr int OFF_PHK = 16 * BLK;
constexpr int OFF_SSM = 20 * BLK;
constexpr int PARK = 14336;
constexpr int OFF_TAB = OFF_SSM + 4 * PARK;
constexpr int OFF_WPHI = OFF_TAB + 4 * 2048;
constexpr int OFF_BAR = OFF_WPHI + 2048;
constexpr int SMEM_BYTES = OFF_BAR + 512;
static_assert(SMEM_BYTES <= 232448, "smem");
DEVINL int o_off(int i) { return i == 5 ? OFF_TAB : ((0x1003BADC >> (4 * i)) & 15) * BLK; }
DEVINL int w_off(int i, int c) {
  return i < 6 ? (((0x432987 >> (4 * i)) & 15) * 2 + c) * BLK : OFF_SSM + ((i - 6) * 2 + c) * PARK;
}

constexpr int SPIN_LIMIT = 1 << 17;

DEVINL uint32_t smem_u32(const void* p) { return (uint32_t)__cvta_generic_to_shared(p); }
DEVINL void mbar_init(uint32_t bar, int cnt) { asm volatile("mbarrier.init.shared::cta.b64 [%0], %1;" ::"r"(bar), "r"(cnt)); }
DEVINL void mbar_expect_tx(uint32_t bar, uint32_t bytes) {
  asm volatile("mbarrier.arrive.expect_tx.shared::cta.b64 _, [%0], %1;" ::"r"(bar), "r"(bytes) : "memory");
}
DEVINL void mbar_arrive(uint32_t bar) { asm volatile("mbarrier.arrive.shared::cta.b64 _, [%0];" ::"r"(bar) : "memory"); }
DEVINL void mbar_wait(uint32_t bar, uint32_t parity) {
  uint32_t ok;
  int it = 0;
  do {
    asm volatile(
        "{\n.reg .pred p;\nmbarrier.try_wait.parity.shared::cta.b64 p, [%1], %2;\nselp.u32 %0, 1, 0, p;\n}\n"
        : "=r"(ok)
        : "r"(bar), "r"(parity)
        : "memory");
    if (++it > SPIN_LIMIT) break;
  } while (!ok);
}
DEVINL void tma_load_2d(uint32_t dst, const CUtensorMap* tm, int c0, int c1, uint32_t bar) {
  asm volatile(
      "cp.async.bulk.tensor.2d.shared::cluster.global.mbarrier::complete_tx::bytes [%0], [%1, {%3, %4}], [%2];"
      ::"r"(dst), "l"(tm), "r"(bar), "r"(c0), "r"(c1)
      : "memory");
}
DEVINL void named_bar(int id, int n) { asm volatile("bar.sync %0, %1;" ::"r"(id), "r"(n) : "memory"); }
DEVINL void wg_fence() { asm volatile("wgmma.fence.sync.aligned;" ::: "memory"); }
DEVINL void wg_commit() { asm volatile("wgmma.commit_group.sync.aligned;" ::: "memory"); }
template <int N>
DEVINL void wg_wait() { asm volatile("wgmma.wait_group.sync.aligned %0;" ::"n"(N) : "memory"); }
DEVINL uint64_t make_desc(uint32_t addr, uint32_t lbo, uint32_t sbo) {
  return (uint64_t)((addr & 0x3FFFF) >> 4) | ((uint64_t)(lbo >> 4) << 16) | ((uint64_t)(sbo >> 4) << 32) | (1ull << 62);
}
DEVINL void mma16816(float (&c)[4], uint32_t a0, uint32_t a1, uint32_t a2, uint32_t a3, uint32_t b0, uint32_t b1) {
  asm volatile(
      "mma.sync.aligned.m16n8k16.row.col.f32.bf16.bf16.f32 {%0,%1,%2,%3}, {%4,%5,%6,%7}, {%8,%9}, {%0,%1,%2,%3};"
      : "+f"(c[0]), "+f"(c[1]), "+f"(c[2]), "+f"(c[3])
      : "r"(a0), "r"(a1), "r"(a2), "r"(a3), "r"(b0), "r"(b1));
}
DEVINL void ldsm_x4(uint32_t& r0, uint32_t& r1, uint32_t& r2, uint32_t& r3, uint32_t addr) {
  asm volatile("ldmatrix.sync.aligned.m8n8.x4.shared.b16 {%0,%1,%2,%3}, [%4];"
               : "=r"(r0), "=r"(r1), "=r"(r2), "=r"(r3) : "r"(addr) : "memory");
}
DEVINL void ldsm_x4_t(uint32_t& r0, uint32_t& r1, uint32_t& r2, uint32_t& r3, uint32_t addr) {
  asm volatile("ldmatrix.sync.aligned.m8n8.x4.trans.shared.b16 {%0,%1,%2,%3}, [%4];"
               : "=r"(r0), "=r"(r1), "=r"(r2), "=r"(r3) : "r"(addr) : "memory");
}
DEVINL void stsm_x4(uint32_t addr, uint32_t r0, uint32_t r1, uint32_t r2, uint32_t r3) {
  asm volatile("stmatrix.sync.aligned.m8n8.x4.shared.b16 [%0], {%1,%2,%3,%4};" ::"r"(addr), "r"(r0), "r"(r1), "r"(r2), "r"(r3) : "memory");
}
DEVINL void stsm_x4_t(uint32_t addr, uint32_t r0, uint32_t r1, uint32_t r2, uint32_t r3) {
  asm volatile("stmatrix.sync.aligned.m8n8.x4.trans.shared.b16 [%0], {%1,%2,%3,%4};" ::"r"(addr), "r"(r0), "r"(r1), "r"(r2), "r"(r3) : "memory");
}
DEVINL uint32_t lds32(uint32_t a) { uint32_t v; asm volatile("ld.shared.b32 %0, [%1];" : "=r"(v) : "r"(a) : "memory"); return v; }
DEVINL uint4 lds128(uint32_t a) {
  uint4 v;
  asm volatile("ld.shared.v4.b32 {%0,%1,%2,%3}, [%4];" : "=r"(v.x), "=r"(v.y), "=r"(v.z), "=r"(v.w) : "r"(a) : "memory");
  return v;
}
DEVINL void sts32(uint32_t a, uint32_t v) { asm volatile("st.shared.b32 [%0], %1;" ::"r"(a), "r"(v) : "memory"); }
DEVINL void sts16(uint32_t a, uint16_t v) { asm volatile("st.shared.b16 [%0], %1;" ::"r"(a), "h"(v) : "memory"); }
DEVINL void sts128(uint32_t a, uint32_t x, uint32_t y, uint32_t z, uint32_t w) {
  asm volatile("st.shared.v4.b32 [%0], {%1,%2,%3,%4};" ::"r"(a), "r"(x), "r"(y), "r"(z), "r"(w) : "memory");
}
DEVINL uint4 ld_relaxed_v4(const void* p) {
  uint4 v;
  asm volatile("ld.relaxed.gpu.global.v4.b32 {%0,%1,%2,%3}, [%4];" : "=r"(v.x), "=r"(v.y), "=r"(v.z), "=r"(v.w) : "l"(p) : "memory");
  return v;
}
DEVINL uint32_t ld_relaxed(const void* p) {
  uint32_t v;
  asm volatile("ld.relaxed.gpu.global.b32 %0, [%1];" : "=r"(v) : "l"(p) : "memory");
  return v;
}
DEVINL uint32_t ld_acquire(const void* p) {
  uint32_t v;
  asm volatile("ld.acquire.gpu.global.b32 %0, [%1];" : "=r"(v) : "l"(p) : "memory");
  return v;
}
DEVINL void st_relaxed_v4(void* p, uint32_t x, uint32_t y, uint32_t z, uint32_t w) {
  asm volatile("st.relaxed.gpu.global.v4.b32 [%0], {%1,%2,%3,%4};" ::"l"(p), "r"(x), "r"(y), "r"(z), "r"(w) : "memory");
}
DEVINL uint32_t pack2(float lo, float hi) {
  uint32_t r;
  asm("cvt.rn.bf16x2.f32 %0, %1, %2;" : "=r"(r) : "f"(hi), "f"(lo));
  return r;
}
DEVINL float bf_lo(uint32_t w) { return __uint_as_float(w << 16); }
DEVINL float bf_hi(uint32_t w) { return __uint_as_float(w & 0xFFFF0000u); }
DEVINL float bf_round(float v) { return __bfloat162float(__float2bfloat16_rn(v)); }
DEVINL uint32_t hmax2(uint32_t a, uint32_t b) { uint32_t r; asm("max.bf16x2 %0, %1, %2;" : "=r"(r) : "r"(a), "r"(b)); return r; }
DEVINL uint32_t hmin2(uint32_t a, uint32_t b) { uint32_t r; asm("min.bf16x2 %0, %1, %2;" : "=r"(r) : "r"(a), "r"(b)); return r; }
DEVINL float ex2f(float x) { float r; asm("ex2.approx.ftz.f32 %0, %1;" : "=f"(r) : "f"(x)); return r; }
DEVINL float rcpf(float x) { float r; asm("rcp.approx.ftz.f32 %0, %1;" : "=f"(r) : "f"(x)); return r; }

__device__ __forceinline__ void wgmma_ss_n192(float (&d)[96], uint64_t da, uint64_t db, int scale_d) {
  asm volatile("{\n.reg .pred p;\nsetp.ne.b32 p, %98, 0;\n"
    "wgmma.mma_async.sync.aligned.m64n192k16.f32.bf16.bf16 "
    "{%0, %1, %2, %3, %4, %5, %6, %7, %8, %9, %10, %11, %12, %13, %14, %15, %16, %17, %18, %19, %20, %21, %22, %23, %24, %25, %26, %27, %28, %29, %30, %31, %32, %33, %34, %35, %36, %37, %38, %39, %40, %41, %42, %43, %44, %45, %46, %47, %48, %49, %50, %51, %52, %53, %54, %55, %56, %57, %58, %59, %60, %61, %62, %63, %64, %65, %66, %67, %68, %69, %70, %71, %72, %73, %74, %75, %76, %77, %78, %79, %80, %81, %82, %83, %84, %85, %86, %87, %88, %89, %90, %91, %92, %93, %94, %95}, %96, %97, p, 1, 1, 0, 1;\n}\n"
    : "+f"(d[0]), "+f"(d[1]), "+f"(d[2]), "+f"(d[3]), "+f"(d[4]), "+f"(d[5]), "+f"(d[6]), "+f"(d[7]), "+f"(d[8]), "+f"(d[9]), "+f"(d[10]), "+f"(d[11]), "+f"(d[12]), "+f"(d[13]), "+f"(d[14]), "+f"(d[15]), "+f"(d[16]), "+f"(d[17]), "+f"(d[18]), "+f"(d[19]), "+f"(d[20]), "+f"(d[21]), "+f"(d[22]), "+f"(d[23]), "+f"(d[24]), "+f"(d[25]), "+f"(d[26]), "+f"(d[27]), "+f"(d[28]), "+f"(d[29]), "+f"(d[30]), "+f"(d[31]), "+f"(d[32]), "+f"(d[33]), "+f"(d[34]), "+f"(d[35]), "+f"(d[36]), "+f"(d[37]), "+f"(d[38]), "+f"(d[39]), "+f"(d[40]), "+f"(d[41]), "+f"(d[42]), "+f"(d[43]), "+f"(d[44]), "+f"(d[45]), "+f"(d[46]), "+f"(d[47]), "+f"(d[48]), "+f"(d[49]), "+f"(d[50]), "+f"(d[51]), "+f"(d[52]), "+f"(d[53]), "+f"(d[54]), "+f"(d[55]), "+f"(d[56]), "+f"(d[57]), "+f"(d[58]), "+f"(d[59]), "+f"(d[60]), "+f"(d[61]), "+f"(d[62]), "+f"(d[63]), "+f"(d[64]), "+f"(d[65]), "+f"(d[66]), "+f"(d[67]), "+f"(d[68]), "+f"(d[69]), "+f"(d[70]), "+f"(d[71]), "+f"(d[72]), "+f"(d[73]), "+f"(d[74]), "+f"(d[75]), "+f"(d[76]), "+f"(d[77]), "+f"(d[78]), "+f"(d[79]), "+f"(d[80]), "+f"(d[81]), "+f"(d[82]), "+f"(d[83]), "+f"(d[84]), "+f"(d[85]), "+f"(d[86]), "+f"(d[87]), "+f"(d[88]), "+f"(d[89]), "+f"(d[90]), "+f"(d[91]), "+f"(d[92]), "+f"(d[93]), "+f"(d[94]), "+f"(d[95])
    : "l"(da), "l"(db), "r"(scale_d));
}

__device__ __forceinline__ void wgmma_ss_n128(float (&d)[64], uint64_t da, uint64_t db, int scale_d) {
  asm volatile("{\n.reg .pred p;\nsetp.ne.b32 p, %66, 0;\n"
    "wgmma.mma_async.sync.aligned.m64n128k16.f32.bf16.bf16 "
    "{%0, %1, %2, %3, %4, %5, %6, %7, %8, %9, %10, %11, %12, %13, %14, %15, %16, %17, %18, %19, %20, %21, %22, %23, %24, %25, %26, %27, %28, %29, %30, %31, %32, %33, %34, %35, %36, %37, %38, %39, %40, %41, %42, %43, %44, %45, %46, %47, %48, %49, %50, %51, %52, %53, %54, %55, %56, %57, %58, %59, %60, %61, %62, %63}, %64, %65, p, 1, 1, 0, 1;\n}\n"
    : "+f"(d[0]), "+f"(d[1]), "+f"(d[2]), "+f"(d[3]), "+f"(d[4]), "+f"(d[5]), "+f"(d[6]), "+f"(d[7]), "+f"(d[8]), "+f"(d[9]), "+f"(d[10]), "+f"(d[11]), "+f"(d[12]), "+f"(d[13]), "+f"(d[14]), "+f"(d[15]), "+f"(d[16]), "+f"(d[17]), "+f"(d[18]), "+f"(d[19]), "+f"(d[20]), "+f"(d[21]), "+f"(d[22]), "+f"(d[23]), "+f"(d[24]), "+f"(d[25]), "+f"(d[26]), "+f"(d[27]), "+f"(d[28]), "+f"(d[29]), "+f"(d[30]), "+f"(d[31]), "+f"(d[32]), "+f"(d[33]), "+f"(d[34]), "+f"(d[35]), "+f"(d[36]), "+f"(d[37]), "+f"(d[38]), "+f"(d[39]), "+f"(d[40]), "+f"(d[41]), "+f"(d[42]), "+f"(d[43]), "+f"(d[44]), "+f"(d[45]), "+f"(d[46]), "+f"(d[47]), "+f"(d[48]), "+f"(d[49]), "+f"(d[50]), "+f"(d[51]), "+f"(d[52]), "+f"(d[53]), "+f"(d[54]), "+f"(d[55]), "+f"(d[56]), "+f"(d[57]), "+f"(d[58]), "+f"(d[59]), "+f"(d[60]), "+f"(d[61]), "+f"(d[62]), "+f"(d[63])
    : "l"(da), "l"(db), "r"(scale_d));
}


constexpr float LOG2E = 1.4426950408889634f;

DEVINL uint32_t hadd2(uint32_t a, uint32_t b) { uint32_t r; asm("add.rn.bf16x2 %0, %1, %2;" : "=r"(r) : "r"(a), "r"(b)); return r; }
DEVINL uint32_t xw(uint32_t a, uint32_t b) { return __byte_perm(a, b, 0x5432); }
DEVINL void red_add(unsigned* p, unsigned v) { asm volatile("red.relaxed.gpu.global.add.u32 [%0], %1;" ::"l"(p), "r"(v) : "memory"); }
DEVINL void wait_cnt(const unsigned* p, unsigned target) {
  int it = 0;
#pragma unroll 1
  while ((int)(ld_relaxed(p) - target) < 0) {
    __nanosleep(64);
    if (++it > SPIN_LIMIT) break;
  }
  (void)ld_acquire(p);
}
DEVINL void sts64(uint32_t a, uint32_t x, uint32_t y) { asm volatile("st.shared.v2.b32 [%0], {%1,%2};" ::"r"(a), "r"(x), "r"(y) : "memory"); }
DEVINL uint2 lds64(uint32_t a) {
  uint2 v;
  asm volatile("ld.shared.v2.b32 {%0,%1}, [%2];" : "=r"(v.x), "=r"(v.y) : "r"(a) : "memory");
  return v;
}
DEVINL void mma16808(float (&c)[4], uint32_t a0, uint32_t a1, uint32_t b0) {
  asm volatile("mma.sync.aligned.m16n8k8.row.col.f32.bf16.bf16.f32 {%0,%1,%2,%3}, {%4,%5}, {%6}, {%0,%1,%2,%3};"
      : "+f"(c[0]), "+f"(c[1]), "+f"(c[2]), "+f"(c[3]) : "r"(a0), "r"(a1), "r"(b0));
}
DEVINL void ldsm_r(uint32_t* r, uint32_t addr) { ldsm_x4(r[0], r[1], r[2], r[3], addr); }
DEVINL void ldsm_tr(uint32_t* r, uint32_t addr) { ldsm_x4_t(r[0], r[1], r[2], r[3], addr); }
DEVINL void lds128_r(uint32_t* r, uint32_t a) { const uint4 v = lds128(a); r[0] = v.x; r[1] = v.y; r[2] = v.z; r[3] = v.w; }
DEVINL void tma_store_2d(const CUtensorMap* tm, uint32_t src, int c0, int c1) {
  asm volatile("cp.async.bulk.tensor.2d.global.shared::cta.bulk_group [%0, {%2, %3}], [%1];"
               ::"l"(tm), "r"(src), "r"(c0), "r"(c1) : "memory");
  asm volatile("cp.async.bulk.commit_group;" ::: "memory");
}

DEVINL void fence_async_global() { asm volatile("fence.proxy.async.global;" ::: "memory"); }

DEVINL int uch(int c) { return (c * 16) ^ ((c & 8) << 1); }
DEVINL void lda(uint32_t* r, uint32_t a) {
  asm volatile("ld.volatile.shared.b32 %0, [%4];\nld.volatile.shared.b32 %1, [%4+32];\nld.volatile.shared.b32 %2, [%4+-32];\nld.volatile.shared.b32 %3, [%4];"
               : "=r"(r[0]), "=r"(r[1]), "=r"(r[2]), "=r"(r[3]) : "r"(a) : "memory");
}
DEVINL void sts128_if(bool on, uint32_t a, uint32_t x, uint32_t y, uint32_t z, uint32_t w) {
  asm volatile("{\n.reg .pred q;\nsetp.ne.u32 q, %5, 0;\n@q st.shared.v4.b32 [%0], {%1,%2,%3,%4};\n}" ::"r"(a), "r"(x), "r"(y), "r"(z), "r"(w), "r"((uint32_t)on) : "memory");
}
DEVINL void red_v4(float4* p, float a, float b, float c) {
  asm volatile("red.relaxed.gpu.global.add.v4.f32 [%0], {%1, %2, %3, %4};" ::"l"(p), "f"(a), "f"(b), "f"(c), "f"(1.f) : "memory");
}
DEVINL unsigned short ldg16_now(const void* p) {
  unsigned short v;
  asm volatile("ld.global.nc.u16 %0, [%1];" : "=h"(v) : "l"(p));
  return v;
}
DEVINL uint32_t hmul2(uint32_t a, uint32_t b) { uint32_t r; asm("mul.rn.bf16x2 %0, %1, %2;" : "=r"(r) : "r"(a), "r"(b)); return r; }
DEVINL uint32_t hfma2(uint32_t a, uint32_t b, uint32_t c) { uint32_t r; asm("fma.rn.bf16x2 %0, %1, %2, %3;" : "=r"(r) : "r"(a), "r"(b), "r"(c)); return r; }
struct cplx { float re, im; };
DEVINL cplx cmul(cplx a, cplx b) { return {a.re * b.re - a.im * b.im, a.re * b.im + a.im * b.re}; }
DEVINL cplx csqr(cplx a) { return {a.re * a.re - a.im * a.im, (a.re + a.re) * a.im}; }
DEVINL cplx cexp_p(float ar2, float ang, float p) {
  const float m = ex2f(ar2 * p), th = ang * p;
  return {m * __cosf(th), m * __sinf(th)};
}

template <int LQ, int E, int K0, int K1>
DEVINL void conv_seg(float (&acc)[16][4], uint32_t (&R)[64], uint32_t arow) {
  constexpr int KST = 32 << LQ;
  ldsm_tr(&R[24], arow);
  ldsm_tr(&R[28], arow + KST);
  float tmp[4][4];
#pragma unroll
  for (int i = 0; i < 4; i++) { tmp[i][0] = tmp[i][1] = tmp[i][2] = tmp[i][3] = 0.f; }
#pragma unroll
  for (int k = K0; k <= K1; k++) {
    const int cur = 24 + 4 * ((k - K0) % 3), nxt = 24 + 4 * ((k - K0 + 2) % 3);
    if (k + 2 <= K1) ldsm_tr(&R[nxt], arow + (k + 2 - K0) * KST);
#pragma unroll
    for (int T = 0; T < 16; T++) {
      const int e = k - (8 >> LQ) * T + 16;
      if (e >= 0 && e < E) {
        if (LQ == 1 && (k & 1)) {
          mma16816(tmp[T & 3], R[cur], R[cur + 1], R[cur + 2], R[cur + 3], R[2 * e], R[2 * e + 1]);
          if (e == E - 1 || k + 1 >= K1) {
#pragma unroll
            for (int i = 0; i < 4; i++) { acc[T][i] += tmp[T & 3][i]; tmp[T & 3][i] = 0.f; }
          }
        } else {
          mma16816(acc[T], R[cur], R[cur + 1], R[cur + 2], R[cur + 3], R[2 * e], R[2 * e + 1]);
        }
      }
    }
  }
}
template <int E>
DEVINL void load_taps(uint32_t (&R)[64], uint32_t ta) {
#pragma unroll
  for (int e = 0; e < E; e++) { R[2 * e] = lds32(ta - e * 32); R[2 * e + 1] = lds32(ta - e * 32 - 16); }
}

__global__ void __launch_bounds__(512, 1)
fused_kernel(const __grid_constant__ CUtensorMap tm_x, const __grid_constant__ CUtensorMap tm_w,
             const __grid_constant__ CUtensorMap tm_wo,
             const __grid_constant__ CUtensorMap tm_out, const __grid_constant__ CUtensorMap tm_os,
             const __grid_constant__ CUtensorMap tm_ol, const __grid_constant__ CUtensorMap tm_xs,
             const __grid_constant__ CUtensorMap tm_xl, const __nv_bfloat16* __restrict__ x,
             const __nv_bfloat16* __restrict__ wphi,
             const __nv_bfloat16* __restrict__ logAr, const __nv_bfloat16* __restrict__ Aim,
             const __nv_bfloat16* __restrict__ Cre, const __nv_bfloat16* __restrict__ Cim,
             const __nv_bfloat16* __restrict__ logdt, const __nv_bfloat16* __restrict__ Dskip,
             const __nv_bfloat16* __restrict__ gatew) {
  extern __shared__ __align__(1024) unsigned char smem[];
  const uint32_t sb = smem_u32(smem);
  const int tid = threadIdx.x, warp = __shfl_sync(0xffffffffu, tid >> 5, 0), lane = tid & 31;
  const int wgi = __shfl_sync(0xffffffffu, tid >> 7, 0);
  const int g = lane >> 2, t = lane & 3;
  const int mi = lane >> 3, l7 = lane & 7;
  const int bid = blockIdx.x;
  const int hg_in = bid & 3, rt = (bid >> 2) & 15, hgblk = bid >> 6;
  const int hg = hgblk * 4 + hg_in;

  const uint32_t bar_full = sb + OFF_BAR;
  const uint32_t bar_empty = sb + OFF_BAR + 32;
  const uint32_t bar_full2 = sb + OFF_BAR + 64;
  const uint32_t bar_empty2 = sb + OFF_BAR + 128;
  const uint32_t bar_y = sb + OFF_BAR + 152;
  const uint32_t bar_vfree = sb + OFF_BAR + 160;
  const uint32_t bar_qfree = sb + OFF_BAR + 168;
  const uint32_t bar_aux = sb + OFF_BAR + 176;
  const uint32_t bar_ssm = sb + OFF_BAR + 184;
  const uint32_t bar_kv = sb + OFF_BAR + 192;
  const uint32_t bar_u = sb + OFF_BAR + 200;
  const uint32_t bar_mdone = sb + OFF_BAR + 208;
  const uint32_t bar_s0 = sb + OFF_BAR + 216;
  const uint32_t bar_xfree = sb + OFF_BAR + 224;
  const uint32_t bar_gw = sb + OFF_BAR + 232;
  const uint32_t bar_kg = sb + OFF_BAR + 240;
  const uint32_t bar_near = sb + OFF_BAR + 256;
  const uint32_t sm_epoch = sb + OFF_BAR + 384;


  if (wgi == 3) asm volatile("setmaxnreg.dec.sync.aligned.u32 64;");
  const int kch = hg * 64 + rt * 4 + (warp & 3);
  unsigned short q[16], rdt = 0;
  if (wgi == 2) {
    rdt = ldg16_now(logdt + kch);
#pragma unroll
    for (int i = 0; i < 4; i++) {
      const int n = kch * 128 + 32 * i + lane;
      q[4 * i] = ldg16_now(logAr + n); q[4 * i + 1] = ldg16_now(Aim + n);
      q[4 * i + 2] = ldg16_now(Cre + n); q[4 * i + 3] = ldg16_now(Cim + n);
    }
  }
  if (tid == 128) {
#pragma unroll
    for (int i = 0; i < 4; i++) mbar_init(bar_full + 8 * i, 1);
    asm volatile("fence.mbarrier_init.release.cluster;" ::: "memory");
#pragma unroll 1
    for (int st = 0; st < 4; st++) {
      const int k0 = (4 * hgblk + ((st + hg_in + 1) & 3)) * 64;
      const uint32_t dst = sb + OFF_RING + st * STAGE_BYTES;
      mbar_expect_tx(bar_full + 8 * st, STAGE_BYTES);
      tma_load_2d(dst, &tm_x, k0, rt * 128, bar_full + 8 * st);
      tma_load_2d(dst + 2 * BLK, &tm_w, hg * 64, k0, bar_full + 8 * st);
      tma_load_2d(dst + 3 * BLK, &tm_w, 512 + hg * 64, k0, bar_full + 8 * st);
      tma_load_2d(dst + 4 * BLK, &tm_w, 1024 + hg * 64, k0, bar_full + 8 * st);
    }
  }
  if (tid == 160) {
    constexpr unsigned long long c0 = 0x1111111188881111ull, c1 = 0x4422881341884414ull;
#pragma unroll
    for (int i = 4; i < 32; i++) mbar_init(sb + OFF_BAR + 8 * i, (int)(((i < 16 ? c0 : c1) >> (4 * (i & 15))) & 15));
    mbar_init(bar_near, 12);
    asm volatile("fence.mbarrier_init.release.cluster;" ::: "memory");
  }
  __syncwarp();
  if (wgi == 2) {
    asm volatile("bar.arrive 0, 512;" ::: "memory");
    asm volatile("setmaxnreg.inc.sync.aligned.u32 160;");
    const int w = warp - 8;
    const int ch = kch;
    const uint32_t park = sb + OFF_SSM + w * PARK;
    const uint32_t park2 = sb + 3 * BLK + w * PARK;
    const uint32_t tab = sb + OFF_TAB + w * 2048;
    const uint32_t ub = sb + OFF_U + w * UST + 512;
    const float dsk = bf_lo(__ldg((const unsigned short*)Dskip + ch));
    uint32_t W[56], R[64];
    float klast = 0.f, ka[5][4];
  auto kstore = [&](const uint32_t* V, uint32_t xb) {
    const uint32_t qa = xb + g * 512 + t * 16, ra = xb + 4096 + g * 256 + t * 8, sa = xb + 6144 + g * 128 + t * 4;
#pragma unroll
    for (int gg = 0; gg < 8; gg++) {
      sts128(qa + ((gg ^ (g & 1)) << 6), V[7 * gg], V[7 * gg + 1], V[7 * gg + 2], V[7 * gg + 3]);
      sts64(ra + ((gg ^ (g & 3)) << 5), V[7 * gg + 4], V[7 * gg + 5]);
      sts32(sa + ((gg ^ g) << 4), V[7 * gg + 6]);
    }
  };
    {
      uint32_t pa[4] = {0, 0, 0, 0}, pc[4] = {0, 0, 0, 0};
      float dt = 1.f;
#pragma unroll 1
      for (int u = 0; u < 4; u++) {
        if (u == 0) {
#pragma unroll
          for (int i = 0; i < 4; i++) { pa[i] = q[4 * i] | ((uint32_t)q[4 * i + 1] << 16); pc[i] = q[4 * i + 2] | ((uint32_t)q[4 * i + 3] << 16); }
          dt = bf_round(expf(bf_lo(rdt)));
        }
        if (u == 3) {
#pragma unroll
          for (int i = 0; i < 56; i++) R[i] = W[i];
        }
        const float fa = bf_lo(pa[0]), fi = bf_hi(pa[0]), fr = bf_lo(pc[0]), fc = bf_hi(pc[0]);
        pa[0] = pa[1]; pa[1] = pa[2]; pa[2] = pa[3]; pc[0] = pc[1]; pc[1] = pc[2]; pc[2] = pc[3];
        const float ar2 = -bf_round(expf(fa)) * dt * LOG2E;
        const float ang = fi * dt;
        const cplx C = {2.f * fr * dt, 2.f * fc * dt};
        const cplx w1 = cexp_p(ar2, ang, 1.f), W128 = cexp_p(ar2, ang, 128.f), m2b = cexp_p(ar2, ang, 244.f);
        const cplx E2 = csqr(w1), m2a = csqr(E2), m3a = csqr(m2a), E16 = csqr(m3a), m3b = cmul(m2b, m2a);
        const cplx W256 = csqr(W128), W512 = csqr(W256), W1024 = csqr(W512), W2048 = csqr(W1024);
        klast += C.re * W2048.re - C.im * W2048.im;
        cplx Al = {1.f, 0.f}, Be = C, S2 = cmul(C, W512), S3 = cmul(C, W1024);
        const uint32_t hc = pack2(W128.re, W128.re), hs = pack2(W128.im, -W128.im);
        const uint32_t oc = pack2(w1.re, w1.re), os2 = pack2(-w1.im, w1.im), bc = pack2(W256.re, W256.re), bs = pack2(-W256.im, W256.im);
#pragma unroll
        for (int gg = 0; gg < 8; gg++) {
          const uint32_t al = pack2(Al.re, -Al.im), be = pack2(Be.re, Be.im), bw = __byte_perm(be, 0, 0x1032);
          W[7 * gg] = al; W[7 * gg + 1] = hfma2(__byte_perm(al, 0, 0x1032), hs, hmul2(al, hc)); W[7 * gg + 2] = be;
          W[7 * gg + 3] = hfma2(bw, os2, hmul2(be, oc)); W[7 * gg + 4] = hfma2(bw, bs, hmul2(be, bc)); W[7 * gg + 5] = pack2(S2.re, S2.im);
          W[7 * gg + 6] = pack2(S3.re, S3.im);
          if (gg < 7) {
            Al = gg ? cmul(Al, E16) : E16;
            Be = cmul(Be, E2);
            S2 = cmul(S2, gg == 3 ? m2b : m2a);
            S3 = cmul(S3, (gg & 1) ? m3b : m3a);
          }
        }
        if (u < 2) kstore(W, park + (u & 1) * 7168);
      }
    }
    asm volatile("bar.sync 3, 160;" ::: "memory");
    mbar_wait(bar_mdone, 0);
    kstore(W, park2);
    kstore(R, park2 + 7168);
#pragma unroll
    for (int s = 0; s < 5; s++) { ka[s][0] = ka[s][1] = ka[s][2] = ka[s][3] = 0.f; }
    __syncwarp();
#pragma unroll 1
    for (int u = 0; u < 4; u++) {
      const uint32_t xb = (u < 2 ? park : park2) + (u & 1) * 7168;
#pragma unroll
      for (int km = 0; km < 8; km++) {
        lds128_r(&R[8 * km], xb + km * 512 + ((lane ^ ((km & 1) << 2)) << 4));
        const uint2 r2 = lds64(xb + 4096 + km * 256 + ((lane ^ ((km & 3) << 2)) << 3));
        R[8 * km + 4] = r2.x; R[8 * km + 5] = r2.y;
        R[8 * km + 6] = lds32(xb + 6144 + km * 128 + ((lane ^ (km << 2)) << 2));
      }
#pragma unroll
      for (int km = 0; km < 8; km++)
#pragma unroll
        for (int s = 0; s < 5; s++) mma16808(ka[s], R[8 * km], R[8 * km + 1], R[8 * km + 2 + s]);
    }
    __syncwarp();
    if (lane == 0) mbar_arrive(bar_kg);
#pragma unroll
    for (int o = 16; o > 0; o >>= 1) klast += __shfl_xor_sync(0xffffffffu, klast, o);
    mbar_wait(bar_gw, 0);
    {
        const uint32_t kw = park + 12160;
        {
          const float k512 = __shfl_sync(0xffffffffu, ka[3][0], 0), k1024 = __shfl_sync(0xffffffffu, ka[4][0], 0);
          if (lane == 0) ka[0][0] += dsk;
          if (lane == 31) ka[2][3] -= k512;
          float plo = __shfl_up_sync(0xffffffffu, ka[1][1], 1), phi = __shfl_up_sync(0xffffffffu, ka[1][3], 1);
          float nlo = __shfl_down_sync(0xffffffffu, ka[2][0], 1), nhi = __shfl_down_sync(0xffffffffu, ka[2][2], 1);
          const float l31 = __shfl_sync(0xffffffffu, ka[1][1], 31), h31 = __shfl_sync(0xffffffffu, ka[1][3], 31);
          const float e0 = __shfl_sync(0xffffffffu, ka[2][2], 0);
          if (lane == 0) { plo = 0.f; phi = l31; }
          if (lane == 31) { nlo = e0; nhi = 0.f; }
          sts128(kw + 64 + lane * 16, pack2(ka[0][0], plo), pack2(ka[1][0], ka[0][0]), pack2(ka[0][1], ka[1][0]), pack2(ka[1][1], ka[0][1]));
          sts128(kw + 576 + lane * 16, pack2(ka[0][2], phi), pack2(ka[1][2], ka[0][2]), pack2(ka[0][3], ka[1][2]), pack2(ka[1][3], ka[0][3]));
          sts128(kw + 1088 + lane * 16, pack2(ka[2][0], lane ? ka[2][0] : h31), pack2(ka[2][0], ka[2][0]), pack2(ka[2][1], ka[2][0]), pack2(nlo, ka[2][1]));
          sts128(kw + 1600 + lane * 16, pack2(ka[2][2], ka[2][2]), pack2(ka[2][2], ka[2][2]), pack2(ka[2][3], ka[2][2]), pack2(nhi, ka[2][3]));
          sts32(kw + (lane < 16 ? lane * 4 : (512 + lane) * 4), 0u);
          const int dd = lane - 16;
          sts32(tab + lane * 4, pack2((dd == -4 || dd == -3) ? -k1024 : 0.f, (dd == -3 || dd == -2) ? -k1024 : 0.f));
          sts32(tab + 128 + lane * 4, pack2((dd == 12 || dd == 13) ? -k1024 : 0.f, (dd == 13 || dd == 14) ? -k1024 : 0.f));
          sts32(tab + 256 + lane * 4, pack2(dd >= 12 ? klast : 0.f, dd >= 13 ? klast : 0.f));
          const uint32_t tw = tab + 512;
#pragma unroll
          for (int s = 0; s < 2; s++) { sts32(tw + s * 512 + lane * 4, 0u); sts32(tw + s * 512 + 384 + lane * 4, 0u); }
          const int i2 = 32 + 2 * g + (t & 1) + 32 * (t >> 1);
          sts32(tw + i2 * 4, pack2(ka[3][1], ka[3][0]));
          sts32(tw + (i2 + 16) * 4, pack2(ka[3][3], ka[3][2]));
          const int i3 = 32 + g + 16 * t;
          sts32(tw + 512 + i3 * 4, pack2(ka[4][1], ka[4][0]));
          sts32(tw + 512 + (i3 + 8) * 4, pack2(ka[4][3], ka[4][2]));
        }
        mbar_wait(bar_u, 0);
        __syncwarp();
#pragma unroll 1
        for (int it = 0; it < 4; it++) {
          uint4 cu[2], nx[2], pv[2];
#pragma unroll
          for (int j = 0; j < 2; j++) {
            const int ci = it * 32 + lane + 96 * j - 16;
            cu[j] = lds128(ub + uch(ci)); nx[j] = lds128(ub + uch(ci + 1)); pv[j] = lds128(ub + uch(ci - 1));
          }
#pragma unroll
          for (int j = 0; j < 2; j++) {
            const int li = it * 32 + lane + 96 * j;
            const uint4 c = cu[j], n = nx[j], v = pv[j];
            const uint32_t xm = xw(v.w, c.x), x0 = xw(c.x, c.y), x1 = xw(c.y, c.z), x2 = xw(c.z, c.w), x3 = xw(c.w, n.x), x4 = xw(n.x, n.y), x5 = xw(n.y, n.z);
            const uint32_t s0 = hadd2(hadd2(xm, x0), c.x), s1 = hadd2(hadd2(x0, x1), c.y), s2 = hadd2(hadd2(x1, x2), c.z), s3 = hadd2(hadd2(x2, x3), c.w);
            const bool lo = j ? li < 211 : it < 3, hi = j ? li < 147 : it < 3;
            sts128_if(lo, park + li * 16, s2, s3, hadd2(hadd2(x3, x4), n.x), hadd2(hadd2(x4, x5), n.y));
            const uint32_t f0 = hadd2(hadd2(v.w, c.y), s0), f1 = hadd2(hadd2(c.x, c.z), s1), f2 = hadd2(hadd2(c.y, c.w), s2), f3 = hadd2(hadd2(c.z, n.x), s3);
            sts128_if(lo, park + 3504 + li * 16, f0, f1, f2, f3);
            const uint32_t h0 = hadd2(hadd2(xw(v.z, v.w), x1), f0), h1 = hadd2(hadd2(xm, x2), f1), h2 = hadd2(hadd2(x0, x3), f2), h3 = hadd2(hadd2(x1, x4), f3);
            sts128_if(hi, park + 6912 + li * 16, h0, h1, h2, h3);
            sts128_if(hi, park + 9344 + li * 16, hadd2(hadd2(v.z, c.z), h0), hadd2(hadd2(v.w, c.w), h1), hadd2(hadd2(c.x, n.x), h2),
                      hadd2(hadd2(c.y, n.y), h3));
          }
        }
        float acc[16][4];
#pragma unroll
        for (int T = 0; T < 16; T++) { acc[T][0] = acc[T][1] = acc[T][2] = acc[T][3] = 0.f; }
        const int c2 = l7 + 8 * (mi >> 1);
        const int r16 = (mi & 1) * 16;
        load_taps<10>(R, tab + 512 + (2 * g + 95 - t) * 4);
        __syncwarp();
        conv_seg<2, 10, -1, 23>(acc, R, park + ((c2 & 1) ? 3504 + ((c2 + 1) >> 1) * 16 : (c2 >> 1) * 16) + 128 + r16);
        load_taps<9>(R, tab + 1024 + (g + 95 - t) * 4);
        conv_seg<3, 9, -1, 7>(acc, R, park + ((c2 & 1) ? 9344 : 6912) + (1 + c2) * 16 + r16);
        __syncwarp();
        {
          const int uc = 2 * (l7 + (lane >> 4) * 8) + (mi & 1);
          const uint32_t kaddr = kw + (16 + g - 2 * t) * 4, caddr = tab + (16 + g - 2 * t) * 4;
          int opq;
          asm volatile("mov.u32 %0, %%nsmid;" : "=r"(opq));
          uint32_t* S = &R[32];
#pragma unroll
          for (int j = 0; j < 5; j++) ldsm_r(&R[4 * j], ub + uch(uc - 14) + j * 512);
          lda(&S[16], caddr + 128);
          lda(&S[20], caddr + 256);
          lda(&S[24], kaddr + 2048);
          lda(&S[28], caddr);
#pragma unroll
          for (int T = 7; T < 16; T++) mma16816(acc[T], S[16], S[17], S[18], S[19], R[2 * T - 14], R[2 * T - 13]);
          mma16816(acc[15], S[20], S[21], S[22], S[23], R[0], R[1]);
#pragma unroll
          for (int j = 0; j < 8; j++) ldsm_r(&R[4 * j], ub + uch(uc) + j * 512);
#pragma unroll
          for (int j = 0; j < 4; j++) lda(&S[4 * j], kaddr + j * 512);
#pragma unroll
          for (int T = 4; T < 16; T++) mma16816(acc[T], S[24], S[25], S[26], S[27], R[2 * T - 8], R[2 * T - 7]);
#pragma unroll
          for (int T = 8; T < 16; T++) mma16816(acc[T], S[28], S[29], S[30], S[31], R[2 * T - 16], R[2 * T - 15]);
          __syncwarp();
          if (lane == 0) mbar_arrive(bar_near);
#pragma unroll 1
          for (int mp = 0; mp < 4; mp++) {
#pragma unroll
            for (int hb = 0; hb < 2; hb++) {
              const int ml = 2 * mp + hb;
              uint32_t* Sc = &S[16 * hb];
              uint32_t* Sn = &S[16 - 16 * hb];
              const uint32_t kp = kaddr + ml * 64 + 64;
              const uint32_t uo = ub + uch(uc - 2 * ml), un = ub + uch(uc - 2 * ml - 2);
              if (opq > 2 * hb) {
                if (hb || true) {
#pragma unroll
                  for (int j = 4; j < 8; j++) ldsm_r(&R[4 * j], uo + j * 512);
                }
#pragma unroll
                for (int j = 0; j < 4; j++) lda(&Sn[4 * j], kp + j * 512);
#pragma unroll
                for (int m = 0; m < 4; m++)
#pragma unroll
                  for (int T = m; T < 8; T++) mma16816(acc[T], Sc[4 * m], Sc[4 * m + 1], Sc[4 * m + 2], Sc[4 * m + 3], R[2 * (T - m)], R[2 * (T - m) + 1]);
              }
              if (opq > 2 * hb + 1) {
                ldsm_r(&R[0], un);
                ldsm_r(&R[4], un + 512);
#pragma unroll
                for (int m = 3; m >= 0; m--) {
#pragma unroll
                  for (int T = 8; T < 16; T++) mma16816(acc[T], Sc[4 * m], Sc[4 * m + 1], Sc[4 * m + 2], Sc[4 * m + 3], R[2 * (T - m)], R[2 * (T - m) + 1]);
                  if (m == 3) ldsm_r(&R[8], un + 2 * 512);
                  if (m == 1) ldsm_r(&R[12], un + 3 * 512);
                }
              }
            }
          }
        }
        __syncwarp();
        if (lane == 0) mbar_arrive(bar_ssm);
        {
          const uint32_t ya = park + 8192 + ((lane >> 4) * 128 + l7 * 16 + (mi & 1) * 8) * 2;
          const uint32_t tag = g == 0 ? 0x00010001u : 0u;
#pragma unroll
          for (int T = 0; T < 16; T += 2)
            stsm_x4_t(ya + T * 256, pack2(acc[T][0], acc[T][1]) | tag, pack2(acc[T][2], acc[T][3]) | tag,
                      pack2(acc[T + 1][0], acc[T + 1][1]) | tag, pack2(acc[T + 1][2], acc[T + 1][3]) | tag);
          mbar_wait(bar_empty2 + 8, 0);
          __syncwarp();
#pragma unroll
          for (int i = 0; i < 8; i++) lds128_r(&R[4 * i], park + 8192 + (i * 32 + lane) * 16);
#pragma unroll
          for (int i = 7; i >= 0; i--)
            st_relaxed_v4((uint4*)(g_yT + (size_t)ch * SEQ) + i * 32 + lane, R[4 * i], R[4 * i + 1], R[4 * i + 2], R[4 * i + 3]);
          uint4* src = (uint4*)(g_yT + (size_t)(hg_in * 128 + w * 32 + mi) * SEQ + rt * 128 + hgblk * 64) + l7;
          uint4 v[8];
#pragma unroll
          for (int i = 0; i < 8; i++) v[i].x = 0;
          __nanosleep(100);
#pragma unroll 1
          for (int it = 0; it < SPIN_LIMIT; it++) {
            uint32_t mn = 0xffffffffu;
#pragma unroll
            for (int i = 0; i < 8; i++)
              if (v[i].x == 0) v[i] = ld_relaxed_v4(src + i * (4 * SEQ / 8));
#pragma unroll
            for (int i = 0; i < 8; i++) mn = min(mn, v[i].x);
            if (mn != 0) break;
          }
          __syncwarp();
          mbar_wait(bar_empty2, 0);
#pragma unroll
          for (int i = 0; i < 8; i++) {
            const int c = w * 32 + i * 4 + mi;
            sts128(sb + 14 * BLK + c * 128 + ((l7 ^ (c & 7)) << 4), v[i].x, v[i].y, v[i].z, v[i].w);
          }
          __syncwarp();
          if (lane == 0) {
            mbar_arrive(bar_y);
          }
        }
    }
  } else if (wgi == 3) {
    if (warp == 12) asm volatile("bar.sync 0, 512;" ::: "memory");
    if (warp == 12) {
#pragma unroll 1
      for (int st = 0; st < 4; st++) {
        mbar_wait(bar_empty + 8 * st, 0);
        if (st == 3) mbar_wait(bar_xfree, 0);
        const int k0 = (4 + st - 4 * hgblk) * 64;
        const uint32_t dst = sb + OFF_RING + st * STAGE_BYTES;
        if (lane == 0) mbar_expect_tx(bar_full + 8 * st, STAGE_BYTES);
        __syncwarp();
        if (lane == 0) tma_load_2d(dst, &tm_x, k0, rt * 128, bar_full + 8 * st);
        else if (lane < 4) tma_load_2d(dst + (1 + lane) * BLK, &tm_w, (lane - 1) * 512 + hg * 64, k0, bar_full + 8 * st);
        __syncwarp();
      }
      mbar_wait(bar_aux, 0);
      {
        const unsigned target = (lds32(sm_epoch) & ~127u) + 128u;
        const uint32_t bar = bar_full2 + 8 * (lane & 7);
        const int cch = (lane + 4 * hgblk) & 7;
        const unsigned* flag = &g_ocnt[(rt * 2 + hgblk) * 8 + cch];
        if (lane < 8) mbar_expect_tx(bar, 3 * BLK);
        mbar_wait(bar_near, 0);
        if (lane < 8) {
          tma_load_2d(sb + w_off(lane, 0), &tm_wo, hg_in * 128, cch * 64, bar);
          tma_load_2d(sb + w_off(lane, 1), &tm_wo, hg_in * 128 + 64, cch * 64, bar);
        }
        __syncwarp();
        mbar_wait(bar_qfree, 0);
        bool need = lane < 8;
#pragma unroll 1
        for (int it = 0; it < SPIN_LIMIT; it++) {
          if (need && (int)(ld_relaxed(flag) - target) >= 0) {
            (void)ld_acquire(flag);
            fence_async_global();
            if (lane < 6) tma_load_2d(sb + o_off(lane), &tm_ol, cch * 64, rt * 128 + hgblk * 64, bar);
            need = false;
          }
          if (!__any_sync(0xffffffffu, need)) break;
          __nanosleep(60);
        }
        mbar_wait(bar_ssm, 0);
        if (lane == 6 || lane == 7) tma_load_2d(sb + o_off(lane), &tm_ol, cch * 64, rt * 128 + hgblk * 64, bar);
        if (lane == 0) red_add(&g_done, 1u);
      }
    } else {
      if (warp == 14) {
        const unsigned done = ld_relaxed(&g_done);
        asm volatile("bar.sync 0, 512;" ::: "memory");
        uint32_t w4[16];
#pragma unroll
        for (int i = 0; i < 16; i++) {
          const unsigned short* wb = (const unsigned short*)wphi + (hg * 4 + (i >> 2)) * 256 + 2 * t * 16 + g + (i & 1) * 128 + ((i >> 1) & 1) * 8;
          w4[i] = (uint32_t)__ldg(wb) | ((uint32_t)__ldg(wb + 16) << 16);
        }
#pragma unroll
        for (int h = 0; h < 4; h++) sts128(sb + OFF_WPHI + h * 512 + lane * 16, w4[4 * h], w4[4 * h + 1], w4[4 * h + 2], w4[4 * h + 3]);
        if (lane == 0) sts32(sm_epoch, done);
        __syncwarp();
        if (lane == 0) mbar_arrive(bar_aux);
        mbar_wait(bar_s0, 0);
#pragma unroll
        for (int i = 0; i < 4; i++) sts128(sb + OFF_U + i * UST + lane * 16, 0, 0, 0, 0);
        __syncwarp();
        if (lane == 0) {
          wait_cnt(&g_xcnt[hg * 32], (done & ~127u) + 128u);
          fence_async_global();
          mbar_expect_tx(bar_u, 16384);
#pragma unroll 1
          for (int i = 0; i < 4; i++) tma_load_2d(sb + OFF_U + i * UST + 512, &tm_xl, 0, (hg * 64 + rt * 4 + i) * 128, bar_u);
        }
        __syncwarp();
      } else {
        const int half = (warp - 13) >> 1;
        const int row0 = rt * 128 + hg * 16 + half * 8;
        const uint4* xr = (const uint4*)(x + (size_t)row0 * DM) + lane;
        float mine = 0.f;
        if (lane < 24) g_kva[hg * 768 + rt * 48 + half * 24 + lane] = make_float4(0.f, 0.f, 0.f, 0.f);
        asm volatile("bar.sync 0, 512;" ::: "memory");
        {
            mbar_wait(bar_full + 24, 0);
            const uint32_t stg = sb + OFF_TAB + half * 4096;
#pragma unroll 1
            for (int rd = 0; rd < 2; rd++) {
              const uint32_t src = sb + OFF_RING + 3 * STAGE_BYTES + (64 * half + 32 * rd + lane) * 128;
              uint32_t r[8][4];
#pragma unroll
              for (int cc = 0; cc < 8; cc++) ldsm_x4(r[cc][0], r[cc][1], r[cc][2], r[cc][3], src + ((cc ^ l7) << 4));
              if (rd == 1) {
                if (lane == 0) asm volatile("cp.async.bulk.wait_group.read 0;" ::: "memory");
                __syncwarp();
              }
#pragma unroll
              for (int cc = 0; cc < 8; cc++) stsm_x4_t(stg + (cc * 8 + l7) * 64 + ((mi ^ ((l7 >> 1) & 3)) << 4), r[cc][0], r[cc][1], r[cc][2], r[cc][3]);
              asm volatile("fence.proxy.async.shared::cta;" ::: "memory");
              __syncwarp();
              if (lane == 0) tma_store_2d(&tm_xs, stg, rt * 128 + 64 * half + 32 * rd, hg * 64);
            }
            if (lane == 0) mbar_arrive(bar_xfree);
            __threadfence();
            __syncwarp();
            if (lane == 0) {
              asm volatile("cp.async.bulk.wait_group 0;" ::: "memory");
              mbar_arrive(bar_gw);
              red_add(&g_xcnt[hg * 32], 4u);
            }
          }
#pragma unroll 1
        for (int b = 0; b < 2; b++) {
          const uint4 gw = __ldg((const uint4*)gatew + b * 32 + lane);
          uint4 a[8];
#pragma unroll
          for (int r = 0; r < 8; r++) a[r] = __ldg(xr + r * 64 + b * 32);
          float sr[8];
#pragma unroll
          for (int r = 0; r < 8; r++) {
            float s = bf_lo(a[r].x) * bf_lo(gw.x);
            s = fmaf(bf_hi(a[r].x), bf_hi(gw.x), s); s = fmaf(bf_lo(a[r].y), bf_lo(gw.y), s); s = fmaf(bf_hi(a[r].y), bf_hi(gw.y), s);
            s = fmaf(bf_lo(a[r].z), bf_lo(gw.z), s); s = fmaf(bf_hi(a[r].z), bf_hi(gw.z), s);
            s = fmaf(bf_lo(a[r].w), bf_lo(gw.w), s); sr[r] = fmaf(bf_hi(a[r].w), bf_hi(gw.w), s);
          }
#pragma unroll
          for (int i = 0; i < 4; i++) sr[i] = ((lane & 16) ? sr[i + 4] : sr[i]) + __shfl_xor_sync(0xffffffffu, (lane & 16) ? sr[i] : sr[i + 4], 16);
#pragma unroll
          for (int i = 0; i < 2; i++) sr[i] = ((lane & 8) ? sr[i + 2] : sr[i]) + __shfl_xor_sync(0xffffffffu, (lane & 8) ? sr[i] : sr[i + 2], 8);
          mine += ((lane & 4) ? sr[1] : sr[0]) + __shfl_xor_sync(0xffffffffu, (lane & 4) ? sr[0] : sr[1], 4);
        }
        mine += __shfl_xor_sync(0xffffffffu, mine, 1);
        mine += __shfl_xor_sync(0xffffffffu, mine, 2);
        if (t == 0) g_gate[row0 + g] = 1.f / (1.f + __expf(-mine));
        {
          uint4* yz = (uint4*)(g_yT + (size_t)(hg_in * 128 + half * 64 + mi) * SEQ + rt * 128 + hgblk * 64) + l7;
#pragma unroll 4
          for (int i = 0; i < 16; i++) yz[i * (4 * SEQ / 8)] = make_uint4(0, 0, 0, 0);
        }
        __threadfence();
        __syncwarp();
        if (lane == 0) red_add(&g_xcnt[(8 + half) * 32], 1u);
      }
      const int idx = (warp - 13) * 32 + lane;
      mbar_wait(bar_vfree, 0);
      {
        const float4* src = g_kva + hg * 768 + idx;
        const bool three = idx < 64;
        uint4 v[9];
#pragma unroll 1
        for (int it = 0; it < SPIN_LIMIT; it++) {
          bool ok = true;
#pragma unroll
          for (int i = 0; i < 9; i++)
            if (i < 6 || three) v[i] = ld_relaxed_v4(src + (i / 3) * 96 + (i % 3) * 256);
#pragma unroll
          for (int i = 0; i < 9; i++)
            if (i < 6 || three) ok = ok && v[i].w == 0x41800000u;
          if (ok) break;
          __nanosleep(100);
        }
        mbar_wait(bar_kg, 0);
#pragma unroll
        for (int r = 0; r < 3; r++) {
          if (r < 2 || three) {
            const int i = idx + 96 * r;
            const uint4 a = v[3 * r], b = v[3 * r + 1], c = v[3 * r + 2];
            sts128(sb + OFF_KV + i * 16, pack2(__uint_as_float(a.x), __uint_as_float(a.y)), pack2(__uint_as_float(a.z), __uint_as_float(b.x)),
                   pack2(__uint_as_float(b.y), __uint_as_float(b.z)), pack2(__uint_as_float(c.x), __uint_as_float(c.y)));
            if (g < 4) sts16(sb + OFF_KV + 4096 + (i >> 5) * 32 + t * 8 + g * 2, (uint16_t)pack2(__uint_as_float(c.z), 0.f));
          }
        }
        __syncwarp();
        if (lane == 0) mbar_arrive(bar_kv);
      }
      if (tid == 448) {
        const unsigned target = (lds32(sm_epoch) & ~127u) + 128u;
        wait_cnt(&g_xcnt[8 * 32], target);
        wait_cnt(&g_xcnt[9 * 32], target);
        mbar_arrive(bar_empty2 + 8);
      }
    }
  } else {
    if (warp == 5) asm volatile("bar.arrive 3, 160;" ::: "memory");
    asm volatile("bar.sync 0, 512;" ::: "memory");
    asm volatile("setmaxnreg.inc.sync.aligned.u32 144;");
    const int wg = wgi, wq = warp & 3;
    const int srow = warp * 16 + l7 + (mi & 1) * 8;
    const int hi16 = lane >> 4;
    const uint32_t ONE = 0x3F803F80u;
    uint32_t kq[8][4];
    {
      float d[96];
#pragma unroll 1
      for (int kc = 0; kc < 8; kc++) {
        const int st = kc & 3;
        mbar_wait(bar_full + 8 * st, kc >> 2);
        const uint32_t sa = sb + OFF_RING + st * STAGE_BYTES + wg * BLK;
        const uint32_t sw = sb + OFF_RING + st * STAGE_BYTES + 2 * BLK;
        wg_fence();
#pragma unroll
        for (int k = 0; k < 4; k++)
          wgmma_ss_n192(d, make_desc(sa + k * 32, 16, 1024), make_desc(sw + k * 2048, BLK, 1024), (kc | k) != 0);
        wg_commit();
        if (kc > 0) {
          wg_wait<1>();
          if (lane == 0) {
            mbar_arrive(bar_empty + 8 * ((kc - 1) & 3));
            if (kc == 5) mbar_arrive(bar_s0);
          }
        }
      }
      wg_wait<0>();
      if (lane == 0) mbar_arrive(bar_mdone);
#pragma unroll
      for (int h = 0; h < 4; h++)
#pragma unroll
        for (int i = 0; i < 4; i++) {
          kq[h][i] = pack2(d[32 + 8 * h + 2 * i], d[33 + 8 * h + 2 * i]);
          kq[4 + h][i] = pack2(d[8 * h + 2 * i], d[8 * h + 2 * i + 1]);
        }
      mbar_wait(bar_mdone, 0);
#pragma unroll
      for (int h = 0; h < 4; h++) {
        const int jv = 64 + 8 * h;
        stsm_x4(sb + OFF_VST + srow * 128 + (((2 * h + hi16) ^ l7) << 4), pack2(d[jv], d[jv + 1]), pack2(d[jv + 2], d[jv + 3]),
                pack2(d[jv + 4], d[jv + 5]), pack2(d[jv + 6], d[jv + 7]));
      }
    }
    mbar_wait(bar_aux, 0);
#pragma unroll 1
    for (int it = 0; it < 2; it++) {
      float ep[4][2][4], en[4][2][4];
      uint32_t lg[4][4];
      float pmin = 1.f;
      {
        uint4 wp[4];
        float c0[4][4], c1[4][4];
#pragma unroll
        for (int j = 0; j < 4; j++) wp[j] = lds128(sb + OFF_WPHI + j * 512 + lane * 16);
#pragma unroll
        for (int j = 0; j < 4; j++) {
#pragma unroll
          for (int i = 0; i < 4; i++) { c0[j][i] = 0.f; c1[j][i] = 0.f; }
          mma16816(c0[j], kq[j][0], kq[j][1], kq[j][2], kq[j][3], wp[j].x, wp[j].y);
          mma16816(c1[j], kq[j][0], kq[j][1], kq[j][2], kq[j][3], wp[j].z, wp[j].w);
        }
#pragma unroll
        for (int j = 0; j < 4; j++) {
          lg[j][0] = pack2(c0[j][0], c0[j][1]); lg[j][1] = pack2(c1[j][0], c1[j][1]);
          lg[j][2] = pack2(c0[j][2], c0[j][3]); lg[j][3] = pack2(c1[j][2], c1[j][3]);
        }
      }
#pragma unroll
      for (int j = 0; j < 4; j++) {
        const uint32_t ma = hmax2(lg[j][0], lg[j][1]), mb = hmax2(lg[j][2], lg[j][3]);
        uint32_t m = hmax2(__byte_perm(ma, mb, 0x5410), __byte_perm(ma, mb, 0x7632));
        m = hmax2(m, __shfl_xor_sync(0xffffffffu, m, 1));
        m = hmax2(m, __shfl_xor_sync(0xffffffffu, m, 2));
#pragma unroll
        for (int r = 0; r < 2; r++) {
          const float ml = -(r ? bf_hi(m) : bf_lo(m)) * LOG2E;
          float* e = ep[j][r];
          e[0] = ex2f(fmaf(bf_lo(lg[j][2 * r]), LOG2E, ml)); e[1] = ex2f(fmaf(bf_hi(lg[j][2 * r]), LOG2E, ml));
          e[2] = ex2f(fmaf(bf_lo(lg[j][2 * r + 1]), LOG2E, ml)); e[3] = ex2f(fmaf(bf_hi(lg[j][2 * r + 1]), LOG2E, ml));
          const float s01 = e[0] * e[1], s23 = e[2] * e[3], pr = s01 * s23, rr = rcpf(pr);
          const float i01 = rr * s23, i23 = rr * s01;
          en[j][r][0] = i01 * e[1]; en[j][r][1] = i01 * e[0]; en[j][r][2] = i23 * e[3]; en[j][r][3] = i23 * e[2];
          pmin = fminf(pmin, pr);
        }
      }
      if (__any_sync(0xffffffffu, !(pmin >= 7.9e-31f))) {
#pragma unroll
        for (int j = 0; j < 4; j++) {
          const uint32_t ma = hmin2(lg[j][0], lg[j][1]), mb = hmin2(lg[j][2], lg[j][3]);
          uint32_t m = hmin2(__byte_perm(ma, mb, 0x5410), __byte_perm(ma, mb, 0x7632));
          m = hmin2(m, __shfl_xor_sync(0xffffffffu, m, 1));
          m = hmin2(m, __shfl_xor_sync(0xffffffffu, m, 2));
#pragma unroll
          for (int r = 0; r < 2; r++) {
            const float ml = (r ? bf_hi(m) : bf_lo(m)) * LOG2E;
            en[j][r][0] = ex2f(fmaf(bf_lo(lg[j][2 * r]), -LOG2E, ml)); en[j][r][1] = ex2f(fmaf(bf_hi(lg[j][2 * r]), -LOG2E, ml));
            en[j][r][2] = ex2f(fmaf(bf_lo(lg[j][2 * r + 1]), -LOG2E, ml)); en[j][r][3] = ex2f(fmaf(bf_hi(lg[j][2 * r + 1]), -LOG2E, ml));
          }
        }
      }
      const uint32_t prow = sb + OFF_PHK + srow * 256;
      uint32_t Pk[4][4], Nk[4][4];
#pragma unroll
      for (int j = 0; j < 4; j++) {
        Pk[j][0] = pack2(ep[j][0][0], ep[j][0][1]); Pk[j][1] = pack2(ep[j][1][0], ep[j][1][1]);
        Pk[j][2] = pack2(ep[j][0][2], ep[j][0][3]); Pk[j][3] = pack2(ep[j][1][2], ep[j][1][3]);
        Nk[j][0] = pack2(en[j][0][0], en[j][0][1]); Nk[j][1] = pack2(en[j][1][0], en[j][1][1]);
        Nk[j][2] = pack2(en[j][0][2], en[j][0][3]); Nk[j][3] = pack2(en[j][1][2], en[j][1][3]);
      }
      if (it == 0) {
        float spa[4][4], sna[4][4];
#pragma unroll
        for (int j = 0; j < 4; j++) {
#pragma unroll
          for (int i = 0; i < 4; i++) { spa[j][i] = 0.f; sna[j][i] = 0.f; }
          mma16816(spa[j], Pk[j][0], Pk[j][1], Pk[j][2], Pk[j][3], ONE, ONE);
          mma16816(sna[j], Nk[j][0], Nk[j][1], Nk[j][2], Nk[j][3], ONE, ONE);
        }
#pragma unroll
        for (int j = 0; j < 4; j++) {
          const float r0 = rcpf(spa[j][0] * sna[j][0]), r1 = rcpf(spa[j][2] * sna[j][2]);
          const uint32_t c0 = pack2(r0 * sna[j][0], r0 * spa[j][0]), c1 = pack2(r1 * sna[j][2], r1 * spa[j][2]);
          const uint32_t p0 = __byte_perm(c0, 0, 0x1010), n0 = __byte_perm(c0, 0, 0x3232), p1 = __byte_perm(c1, 0, 0x1010), n1 = __byte_perm(c1, 0, 0x3232);
          Pk[j][0] = hmul2(Pk[j][0], p0); Pk[j][1] = hmul2(Pk[j][1], p1); Pk[j][2] = hmul2(Pk[j][2], p0); Pk[j][3] = hmul2(Pk[j][3], p1);
          Nk[j][0] = hmul2(Nk[j][0], n0); Nk[j][1] = hmul2(Nk[j][1], n1); Nk[j][2] = hmul2(Nk[j][2], n0); Nk[j][3] = hmul2(Nk[j][3], n1);
          stsm_x4(prow + (((4 * j + hi16) ^ l7) << 4), Pk[j][0], Pk[j][1], Pk[j][2], Pk[j][3]);
          stsm_x4(prow + (((4 * j + 2 + hi16) ^ l7) << 4), Nk[j][0], Nk[j][1], Nk[j][2], Nk[j][3]);
        }
#pragma unroll
        for (int i = 0; i < 16; i++) kq[i >> 2][i & 3] = kq[(i >> 2) + 4][i & 3];
      } else {
#pragma unroll
        for (int i = 0; i < 16; i++) { kq[i >> 2][i & 3] = Pk[i >> 2][i & 3]; kq[4 + (i >> 2)][i & 3] = Nk[i >> 2][i & 3]; }
      }
      if (it == 0) {
        named_bar(1, 256);
        const int hh = warp >> 1, ks = warp & 1;
        float D[2][4][4];
#pragma unroll
        for (int i = 0; i < 8; i++) { D[i >> 2][i & 3][0] = D[i >> 2][i & 3][1] = D[i >> 2][i & 3][2] = D[i >> 2][i & 3][3] = 0.f; }
        const uint32_t va = sb + OFF_VST + (l7 + (mi >> 1) * 8) * 128 + (((2 * hh + (mi & 1)) ^ l7) << 4);
        const uint32_t pa = sb + OFF_PHK + (l7 + (mi & 1) * 8) * 256 + (((4 * hh + 2 * ks + (mi >> 1)) ^ l7) << 4);
        uint32_t A[8][4], B[8][4];
#pragma unroll
        for (int s = 0; s < 8; s++) {
          ldsm_x4_t(A[s][0], A[s][1], A[s][2], A[s][3], va + s * 16 * 128);
          ldsm_x4_t(B[s][0], B[s][1], B[s][2], B[s][3], pa + s * 16 * 256);
        }
#pragma unroll
        for (int s = 0; s < 8; s++) {
          mma16816(D[s & 1][0], A[s][0], A[s][1], A[s][2], A[s][3], B[s][0], B[s][1]);
          mma16816(D[s & 1][1], A[s][0], A[s][1], A[s][2], A[s][3], B[s][2], B[s][3]);
          if (s & 1) {
            mma16816(D[(s >> 1) & 1][2], ONE, ONE, ONE, ONE, hadd2(B[s][0], B[s - 1][0]), hadd2(B[s][1], B[s - 1][1]));
            mma16816(D[(s >> 1) & 1][3], ONE, ONE, ONE, ONE, hadd2(B[s][2], B[s - 1][2]), hadd2(B[s][3], B[s - 1][3]));
          }
        }
        const float zz = (g & 2) ? ((g & 1) ? D[0][3][1] + D[1][3][1] : D[0][3][0] + D[1][3][0])
                                 : ((g & 1) ? D[0][2][1] + D[1][2][1] : D[0][2][0] + D[1][2][0]);
        float4* kp = g_kva + hg * 768 + tid;
        mbar_wait(bar_u, 0);
        red_v4(kp, D[0][0][0] + D[1][0][0], D[0][0][1] + D[1][0][1], D[0][1][0] + D[1][1][0]);
        red_v4(kp + 256, D[0][1][1] + D[1][1][1], D[0][0][2] + D[1][0][2], D[0][0][3] + D[1][0][3]);
        red_v4(kp + 512, D[0][1][2] + D[1][1][2], D[0][1][3] + D[1][1][3], zz);
        __syncwarp();
        if (lane == 0) { mbar_arrive(bar_vfree); mbar_arrive(bar_near); }
      }
    }
    const int row0 = rt * 128 + hgblk * 64 + wq * 16 + g;
    uint32_t gv0 = 0, gv1 = 0;
    const uint32_t os = sb + OFF_PHQ + warp * 2048;
    {
      uint32_t ow[4][4];
      mbar_wait(bar_kv, 0);
      uint4 kP[4], kN[4];
      uint2 zP[4], zN[4];
#pragma unroll
      for (int h = 0; h < 4; h++) {
        zP[h] = lds64(sb + OFF_KV + 4096 + h * 64 + t * 8); zN[h] = lds64(sb + OFF_KV + 4096 + h * 64 + 32 + t * 8);
        kP[h] = lds128(sb + OFF_KV + h * 1024 + lane * 16);
        kN[h] = lds128(sb + OFF_KV + h * 1024 + 512 + lane * 16);
      }
#pragma unroll
      for (int h = 0; h < 4; h++) {
        float P0[4] = {0.f, 0.f, 0.f, 0.f}, P1[4] = {0.f, 0.f, 0.f, 0.f}, PZ[4] = {0.f, 0.f, 0.f, 0.f};
        float N0[4] = {0.f, 0.f, 0.f, 0.f}, N1[4] = {0.f, 0.f, 0.f, 0.f}, NZ[4] = {0.f, 0.f, 0.f, 0.f};
        mma16816(PZ, kq[h][0], kq[h][1], kq[h][2], kq[h][3], (g & 1) ? ONE : zP[h].x, (g & 1) ? ONE : zP[h].y);
        mma16816(NZ, kq[4 + h][0], kq[4 + h][1], kq[4 + h][2], kq[4 + h][3], (g & 1) ? ONE : zN[h].x, (g & 1) ? ONE : zN[h].y);
        mma16816(P0, kq[h][0], kq[h][1], kq[h][2], kq[h][3], kP[h].x, kP[h].y);
        mma16816(P1, kq[h][0], kq[h][1], kq[h][2], kq[h][3], kP[h].z, kP[h].w);
        mma16816(N0, kq[4 + h][0], kq[4 + h][1], kq[4 + h][2], kq[4 + h][3], kN[h].x, kN[h].y);
        mma16816(N1, kq[4 + h][0], kq[4 + h][1], kq[4 + h][2], kq[4 + h][3], kN[h].z, kN[h].w);
#pragma unroll
        for (int r = 0; r < 2; r++) {
          const float rn = rcpf(NZ[2 * r + 1]), sp = PZ[2 * r + 1] * rn;
          const float id = rcpf(fmaf(NZ[2 * r], sp, fmaf(1e-6f, PZ[2 * r + 1], PZ[2 * r])));
          const float fN = sp * id;
          ow[h][r] = pack2(fmaf(P0[2 * r], id, N0[2 * r] * fN), fmaf(P0[2 * r + 1], id, N0[2 * r + 1] * fN));
          ow[h][2 + r] = pack2(fmaf(P1[2 * r], id, N1[2 * r] * fN), fmaf(P1[2 * r + 1], id, N1[2 * r + 1] * fN));
        }
      }
#pragma unroll
      for (int h = 0; h < 4; h++)
        stsm_x4(os + (l7 + (mi & 1) * 8) * 128 + (((2 * h + hi16) ^ l7) << 4), ow[h][0], ow[h][1], ow[h][2], ow[h][3]);
      asm volatile("fence.proxy.async.shared::cta;" ::: "memory");
      __syncwarp();
      if (lane == 0) {
        tma_store_2d(&tm_os, os, hg * 64, rt * 128 + warp * 16);
        asm volatile("cp.async.bulk.wait_group 0;" ::: "memory");
        if (wg == 0) mbar_arrive(bar_qfree);
        fence_async_global();
        red_add(&g_ocnt[(rt * 2 + wg) * 8 + hg], 32u);
      }
      __syncwarp();
    }
    {
    float acc[64];
    if (wg == 0) {
      mbar_wait(bar_full2 + 24, 0);
      gv0 = ld_relaxed(&g_gate[row0]); gv1 = ld_relaxed(&g_gate[row0 + 8]);
    }
#pragma unroll 1
    for (int i = 8 * wg; i < 8; i++) {
      if (i == 1) mbar_wait(bar_ssm, 0);
      mbar_wait(bar_full2 + 8 * i, 0);
      const uint32_t sa = sb + o_off(i), sw = sb + w_off(i, 0), lbo = i < 6 ? BLK : PARK;
      wg_fence();
#pragma unroll
      for (int k = 0; k < 4; k++) wgmma_ss_n128(acc, make_desc(sa + k * 32, 16, 1024), make_desc(sw + k * 2048, lbo, 1024), (i | k) != 0);
      wg_commit();
      if (i > 0) {
        wg_wait<1>();
        if (i == 1 && lane == 0) mbar_arrive(bar_empty2);
      }
    }
    if (wg == 0) mbar_wait(bar_y, 0);
    {
      const float g0 = __uint_as_float(gv0), g1 = __uint_as_float(gv1);
      const float h0 = 1.f - g0, h1 = 1.f - g1;
      const uint32_t ya = sb + 14 * BLK + ((mi >> 1) * 8 + l7) * 128 + (((2 * wq + (mi & 1)) ^ l7) << 4);
      uint32_t y[8][4];
#pragma unroll
      for (int np = 0; np < 8; np++) ldsm_x4_t(y[np][0], y[np][1], y[np][2], y[np][3], ya + np * 16 * 128);
      wg_wait<0>();
      const uint32_t ob = wg ? os : sb + 4 * BLK + wq * 2048;
      const uint32_t oa = ob + (l7 + (mi & 1) * 8) * 128;
#pragma unroll
      for (int np = 0; np < 8; np++) {
        const int j = np * 8;
        stsm_x4(oa + (wg ? 0 : (np >> 2) * BLK) + (((2 * (np & 3) + hi16) ^ l7) << 4),
                pack2(fmaf(g0, acc[j], h0 * bf_lo(y[np][0])), fmaf(g0, acc[j + 1], h0 * bf_hi(y[np][0]))),
                pack2(fmaf(g1, acc[j + 2], h1 * bf_lo(y[np][1])), fmaf(g1, acc[j + 3], h1 * bf_hi(y[np][1]))),
                pack2(fmaf(g0, acc[j + 4], h0 * bf_lo(y[np][2])), fmaf(g0, acc[j + 5], h0 * bf_hi(y[np][2]))),
                pack2(fmaf(g1, acc[j + 6], h1 * bf_lo(y[np][3])), fmaf(g1, acc[j + 7], h1 * bf_hi(y[np][3]))));
      }
      asm volatile("fence.proxy.async.shared::cta;" ::: "memory");
      __syncwarp();
      if (lane == 0 && wg == 1) mbar_arrive(bar_qfree);
      if (lane == 0 && wg == 0) {
        tma_store_2d(&tm_out, ob, hg_in * 128, rt * 128 + hgblk * 64 + wq * 16);
        tma_store_2d(&tm_out, ob + BLK, hg_in * 128 + 64, rt * 128 + hgblk * 64 + wq * 16);
        asm volatile("cp.async.bulk.wait_group.read 0;" ::: "memory");
      }
    }
    }
  }
}

typedef CUresult (*EncodeFn)(CUtensorMap*, CUtensorMapDataType, cuuint32_t, void*, const cuuint64_t*, const cuuint64_t*,
                             const cuuint32_t*, const cuuint32_t*, CUtensorMapInterleave, CUtensorMapSwizzle,
                             CUtensorMapL2promotion, CUtensorMapFloatOOBfill);

void make_map(EncodeFn fn, CUtensorMap* m, const void* p, uint64_t cols, uint64_t rows, uint32_t bc, uint32_t br,
              CUtensorMapSwizzle sw = CU_TENSOR_MAP_SWIZZLE_128B) {
  cuuint64_t dims[2] = {cols, rows};
  cuuint64_t strides[1] = {cols * 2};
  cuuint32_t box[2] = {bc, br};
  cuuint32_t es[2] = {1, 1};
  fn(m, CU_TENSOR_MAP_DATA_TYPE_BFLOAT16, 2, const_cast<void*>(p), dims, strides, box, es, CU_TENSOR_MAP_INTERLEAVE_NONE,
     sw, CU_TENSOR_MAP_L2_PROMOTION_L2_128B, CU_TENSOR_MAP_FLOAT_OOB_FILL_NONE);
}

}

extern "C" void kernel_launch(void* const* d_in, const int* in_sizes, int n_in, void* d_out, int out_size) {
  (void)in_sizes; (void)n_in; (void)out_size;
  static EncodeFn fn = nullptr;
  static void* optr = nullptr;
  static void* xptr = nullptr;
  if (!fn) {
    void* p = nullptr;
    cudaDriverEntryPointQueryResult st;
    cudaGetDriverEntryPoint("cuTensorMapEncodeTiled", &p, cudaEnableDefault, &st);
    fn = (EncodeFn)p;
    cudaGetSymbolAddress(&optr, g_o);
    cudaGetSymbolAddress(&xptr, g_xT);
    cudaFuncSetAttribute(fused_kernel, cudaFuncAttributeMaxDynamicSharedMemorySize, SMEM_BYTES);
  }
  typedef const __nv_bfloat16* bp;
  CUtensorMap tx, tw, two, to, tos, tol, txs, txl;
  make_map(fn, &tx, d_in[0], 512, 2048, 64, 128);
  make_map(fn, &tw, d_in[1], 1536, 512, 64, 64);
  make_map(fn, &two, d_in[3], 512, 512, 64, 64);
  make_map(fn, &to, d_out, 512, 2048, 64, 16);
  make_map(fn, &tos, optr, 512, 2048, 64, 16);
  make_map(fn, &tol, optr, 512, 2048, 64, 64);
  make_map(fn, &txs, xptr, 2048, 512, 32, 64, CU_TENSOR_MAP_SWIZZLE_64B);
  make_map(fn, &txl, xptr, 16, 65536, 16, 128, CU_TENSOR_MAP_SWIZZLE_32B);
  fused_kernel<<<NCTA, 512, SMEM_BYTES, cudaStreamPerThread>>>(
      tx, tw, two, to, tos, tol, txs, txl, (bp)d_in[0], (bp)d_in[2], (bp)d_in[5], (bp)d_in[6], (bp)d_in[7], (bp)d_in[8], (bp)d_in[9],
      (bp)d_in[10], (bp)d_in[11]);
}
```

```cpp
#include <cuda_runtime.h>
#include <cuda_bf16.h>
#include <cuda.h>
#include <stdint.h>

#define DEVINL __device__ __forceinline__

namespace {

constexpr int SEQ = 2048;
constexpr int DM = 512;
constexpr int NCTA = 128;

__device__ float4 g_kva[8 * 768];
__device__ float g_gate[SEQ];
__device__ __align__(1024) __nv_bfloat16 g_o[SEQ * DM];
__device__ __align__(1024) __nv_bfloat16 g_yT[DM * SEQ];
__device__ __align__(1024) __nv_bfloat16 g_xT[DM * SEQ];
__device__ unsigned g_done;
__device__ unsigned g_xcnt[10 * 32];
__device__ unsigned g_ocnt[16 * 2 * 8];

constexpr int BLK = 8192;
constexpr int STAGE_BYTES = 5 * BLK;
constexpr int OFF_RING = 0;
constexpr int OFF_U = 0;
constexpr int UST = 4608;
constexpr int OFF_KV = 3 * BLK;
constexpr int OFF_PHQ = 10 * BLK;
constexpr int OFF_VST = 14 * BLK;
constexpr int OFF_PHK = 16 * BLK;
constexpr int OFF_SSM = 20 * BLK;
constexpr int PARK = 14336;
constexpr int OFF_TAB = OFF_SSM + 4 * PARK;
constexpr int OFF_WPHI = OFF_TAB + 4 * 2048;
constexpr int OFF_BAR = OFF_WPHI + 2048;
constexpr int SMEM_BYTES = OFF_BAR + 512;
static_assert(SMEM_BYTES <= 232448, "smem");
DEVINL int o_off(int i) { return i == 5 ? OFF_TAB : ((0x1003BADC >> (4 * i)) & 15) * BLK; }
DEVINL int w_off(int i, int c) {
  return i < 6 ? (((0x432987 >> (4 * i)) & 15) * 2 + c) * BLK : OFF_SSM + ((i - 6) * 2 + c) * PARK;
}

constexpr int SPIN_LIMIT = 1 << 17;

DEVINL uint32_t smem_u32(const void* p) { return (uint32_t)__cvta_generic_to_shared(p); }
DEVINL void mbar_init(uint32_t bar, int cnt) { asm volatile("mbarrier.init.shared::cta.b64 [%0], %1;" ::"r"(bar), "r"(cnt)); }
DEVINL void mbar_expect_tx(uint32_t bar, uint32_t bytes) {
  asm volatile("mbarrier.arrive.expect_tx.shared::cta.b64 _, [%0], %1;" ::"r"(bar), "r"(bytes) : "memory");
}
DEVINL void mbar_arrive(uint32_t bar) { asm volatile("mbarrier.arrive.shared::cta.b64 _, [%0];" ::"r"(bar) : "memory"); }
DEVINL void mbar_wait(uint32_t bar, uint32_t parity) {
  uint32_t ok;
  int it = 0;
  do {
    asm volatile(
        "{\n.reg .pred p;\nmbarrier.try_wait.parity.shared::cta.b64 p, [%1], %2;\nselp.u32 %0, 1, 0, p;\n}\n"
        : "=r"(ok)
        : "r"(bar), "r"(parity)
        : "memory");
    if (++it > SPIN_LIMIT) break;
  } while (!ok);
}
DEVINL void tma_load_2d(uint32_t dst, const CUtensorMap* tm, int c0, int c1, uint32_t bar) {
  asm volatile(
      "cp.async.bulk.tensor.2d.shared::cluster.global.mbarrier::complete_tx::bytes [%0], [%1, {%3, %4}], [%2];"
      ::"r"(dst), "l"(tm), "r"(bar), "r"(c0), "r"(c1)
      : "memory");
}
DEVINL void named_bar(int id, int n) { asm volatile("bar.sync %0, %1;" ::"r"(id), "r"(n) : "memory"); }
DEVINL void wg_fence() { asm volatile("wgmma.fence.sync.aligned;" ::: "memory"); }
DEVINL void wg_commit() { asm volatile("wgmma.commit_group.sync.aligned;" ::: "memory"); }
template <int N>
DEVINL void wg_wait() { asm volatile("wgmma.wait_group.sync.aligned %0;" ::"n"(N) : "memory"); }
DEVINL uint64_t make_desc(uint32_t addr, uint32_t lbo, uint32_t sbo) {
  return (uint64_t)((addr & 0x3FFFF) >> 4) | ((uint64_t)(lbo >> 4) << 16) | ((uint64_t)(sbo >> 4) << 32) | (1ull << 62);
}
DEVINL void mma16816(float (&c)[4], uint32_t a0, uint32_t a1, uint32_t a2, uint32_t a3, uint32_t b0, uint32_t b1) {
  asm volatile(
      "mma.sync.aligned.m16n8k16.row.col.f32.bf16.bf16.f32 {%0,%1,%2,%3}, {%4,%5,%6,%7}, {%8,%9}, {%0,%1,%2,%3};"
      : "+f"(c[0]), "+f"(c[1]), "+f"(c[2]), "+f"(c[3])
      : "r"(a0), "r"(a1), "r"(a2), "r"(a3), "r"(b0), "r"(b1));
}
DEVINL void ldsm_x4(uint32_t& r0, uint32_t& r1, uint32_t& r2, uint32_t& r3, uint32_t addr) {
  asm volatile("ldmatrix.sync.aligned.m8n8.x4.shared.b16 {%0,%1,%2,%3}, [%4];"
               : "=r"(r0), "=r"(r1), "=r"(r2), "=r"(r3) : "r"(addr) : "memory");
}
DEVINL void ldsm_x4_t(uint32_t& r0, uint32_t& r1, uint32_t& r2, uint32_t& r3, uint32_t addr) {
  asm volatile("ldmatrix.sync.aligned.m8n8.x4.trans.shared.b16 {%0,%1,%2,%3}, [%4];"
               : "=r"(r0), "=r"(r1), "=r"(r2), "=r"(r3) : "r"(addr) : "memory");
}
DEVINL void stsm_x4(uint32_t addr, uint32_t r0, uint32_t r1, uint32_t r2, uint32_t r3) {
  asm volatile("stmatrix.sync.aligned.m8n8.x4.shared.b16 [%0], {%1,%2,%3,%4};" ::"r"(addr), "r"(r0), "r"(r1), "r"(r2), "r"(r3) : "memory");
}
DEVINL void stsm_x4_t(uint32_t addr, uint32_t r0, uint32_t r1, uint32_t r2, uint32_t r3) {
  asm volatile("stmatrix.sync.aligned.m8n8.x4.trans.shared.b16 [%0], {%1,%2,%3,%4};" ::"r"(addr), "r"(r0), "r"(r1), "r"(r2), "r"(r3) : "memory");
}
DEVINL uint32_t lds32(uint32_t a) { uint32_t v; asm volatile("ld.shared.b32 %0, [%1];" : "=r"(v) : "r"(a) : "memory"); return v; }
DEVINL uint4 lds128(uint32_t a) {
  uint4 v;
  asm volatile("ld.shared.v4.b32 {%0,%1,%2,%3}, [%4];" : "=r"(v.x), "=r"(v.y), "=r"(v.z), "=r"(v.w) : "r"(a) : "memory");
  return v;
}
DEVINL void sts32(uint32_t a, uint32_t v) { asm volatile("st.shared.b32 [%0], %1;" ::"r"(a), "r"(v) : "memory"); }
DEVINL void sts16(uint32_t a, uint16_t v) { asm volatile("st.shared.b16 [%0], %1;" ::"r"(a), "h"(v) : "memory"); }
DEVINL void sts128(uint32_t a, uint32_t x, uint32_t y, uint32_t z, uint32_t w) {
  asm volatile("st.shared.v4.b32 [%0], {%1,%2,%3,%4};" ::"r"(a), "r"(x), "r"(y), "r"(z), "r"(w) : "memory");
}
DEVINL uint4 ld_relaxed_v4(const void* p) {
  uint4 v;
  asm volatile("ld.relaxed.gpu.global.v4.b32 {%0,%1,%2,%3}, [%4];" : "=r"(v.x), "=r"(v.y), "=r"(v.z), "=r"(v.w) : "l"(p) : "memory");
  return v;
}
DEVINL uint32_t ld_relaxed(const void* p) {
  uint32_t v;
  asm volatile("ld.relaxed.gpu.global.b32 %0, [%1];" : "=r"(v) : "l"(p) : "memory");
  return v;
}
DEVINL uint32_t ld_acquire(const void* p) {
  uint32_t v;
  asm volatile("ld.acquire.gpu.global.b32 %0, [%1];" : "=r"(v) : "l"(p) : "memory");
  return v;
}
DEVINL void st_relaxed_v4(void* p, uint32_t x, uint32_t y, uint32_t z, uint32_t w) {
  asm volatile("st.relaxed.gpu.global.v4.b32 [%0], {%1,%2,%3,%4};" ::"l"(p), "r"(x), "r"(y), "r"(z), "r"(w) : "memory");
}
DEVINL uint32_t pack2(float lo, float hi) {
  uint32_t r;
  asm("cvt.rn.bf16x2.f32 %0, %1, %2;" : "=r"(r) : "f"(hi), "f"(lo));
  return r;
}
DEVINL float bf_lo(uint32_t w) { return __uint_as_float(w << 16); }
DEVINL float bf_hi(uint32_t w) { return __uint_as_float(w & 0xFFFF0000u); }
DEVINL float bf_round(float v) { return __bfloat162float(__float2bfloat16_rn(v)); }
DEVINL uint32_t hmax2(uint32_t a, uint32_t b) { uint32_t r; asm("max.bf16x2 %0, %1, %2;" : "=r"(r) : "r"(a), "r"(b)); return r; }
DEVINL uint32_t hmin2(uint32_t a, uint32_t b) { uint32_t r; asm("min.bf16x2 %0, %1, %2;" : "=r"(r) : "r"(a), "r"(b)); return r; }
DEVINL float ex2f(float x) { float r; asm("ex2.approx.ftz.f32 %0, %1;" : "=f"(r) : "f"(x)); return r; }
DEVINL float rcpf(float x) { float r; asm("rcp.approx.ftz.f32 %0, %1;" : "=f"(r) : "f"(x)); return r; }

__device__ __forceinline__ void wgmma_ss_n192(float (&d)[96], uint64_t da, uint64_t db, int scale_d) {
  asm volatile("{\n.reg .pred p;\nsetp.ne.b32 p, %98, 0;\n"
    "wgmma.mma_async.sync.aligned.m64n192k16.f32.bf16.bf16 "
    "{%0, %1, %2, %3, %4, %5, %6, %7, %8, %9, %10, %11, %12, %13, %14, %15, %16, %17, %18, %19, %20, %21, %22, %23, %24, %25, %26, %27, %28, %29, %30, %31, %32, %33, %34, %35, %36, %37, %38, %39, %40, %41, %42, %43, %44, %45, %46, %47, %48, %49, %50, %51, %52, %53, %54, %55, %56, %57, %58, %59, %60, %61, %62, %63, %64, %65, %66, %67, %68, %69, %70, %71, %72, %73, %74, %75, %76, %77, %78, %79, %80, %81, %82, %83, %84, %85, %86, %87, %88, %89, %90, %91, %92, %93, %94, %95}, %96, %97, p, 1, 1, 0, 1;\n}\n"
    : "+f"(d[0]), "+f"(d[1]), "+f"(d[2]), "+f"(d[3]), "+f"(d[4]), "+f"(d[5]), "+f"(d[6]), "+f"(d[7]), "+f"(d[8]), "+f"(d[9]), "+f"(d[10]), "+f"(d[11]), "+f"(d[12]), "+f"(d[13]), "+f"(d[14]), "+f"(d[15]), "+f"(d[16]), "+f"(d[17]), "+f"(d[18]), "+f"(d[19]), "+f"(d[20]), "+f"(d[21]), "+f"(d[22]), "+f"(d[23]), "+f"(d[24]), "+f"(d[25]), "+f"(d[26]), "+f"(d[27]), "+f"(d[28]), "+f"(d[29]), "+f"(d[30]), "+f"(d[31]), "+f"(d[32]), "+f"(d[33]), "+f"(d[34]), "+f"(d[35]), "+f"(d[36]), "+f"(d[37]), "+f"(d[38]), "+f"(d[39]), "+f"(d[40]), "+f"(d[41]), "+f"(d[42]), "+f"(d[43]), "+f"(d[44]), "+f"(d[45]), "+f"(d[46]), "+f"(d[47]), "+f"(d[48]), "+f"(d[49]), "+f"(d[50]), "+f"(d[51]), "+f"(d[52]), "+f"(d[53]), "+f"(d[54]), "+f"(d[55]), "+f"(d[56]), "+f"(d[57]), "+f"(d[58]), "+f"(d[59]), "+f"(d[60]), "+f"(d[61]), "+f"(d[62]), "+f"(d[63]), "+f"(d[64]), "+f"(d[65]), "+f"(d[66]), "+f"(d[67]), "+f"(d[68]), "+f"(d[69]), "+f"(d[70]), "+f"(d[71]), "+f"(d[72]), "+f"(d[73]), "+f"(d[74]), "+f"(d[75]), "+f"(d[76]), "+f"(d[77]), "+f"(d[78]), "+f"(d[79]), "+f"(d[80]), "+f"(d[81]), "+f"(d[82]), "+f"(d[83]), "+f"(d[84]), "+f"(d[85]), "+f"(d[86]), "+f"(d[87]), "+f"(d[88]), "+f"(d[89]), "+f"(d[90]), "+f"(d[91]), "+f"(d[92]), "+f"(d[93]), "+f"(d[94]), "+f"(d[95])
    : "l"(da), "l"(db), "r"(scale_d));
}

__device__ __forceinline__ void wgmma_ss_n128(float (&d)[64], uint64_t da, uint64_t db, int scale_d) {
  asm volatile("{\n.reg .pred p;\nsetp.ne.b32 p, %66, 0;\n"
    "wgmma.mma_async.sync.aligned.m64n128k16.f32.bf16.bf16 "
    "{%0, %1, %2, %3, %4, %5, %6, %7, %8, %9, %10, %11, %12, %13, %14, %15, %16, %17, %18, %19, %20, %21, %22, %23, %24, %25, %26, %27, %28, %29, %30, %31, %32, %33, %34, %35, %36, %37, %38, %39, %40, %41, %42, %43, %44, %45, %46, %47, %48, %49, %50, %51, %52, %53, %54, %55, %56, %57, %58, %59, %60, %61, %62, %63}, %64, %65, p, 1, 1, 0, 1;\n}\n"
    : "+f"(d[0]), "+f"(d[1]), "+f"(d[2]), "+f"(d[3]), "+f"(d[4]), "+f"(d[5]), "+f"(d[6]), "+f"(d[7]), "+f"(d[8]), "+f"(d[9]), "+f"(d[10]), "+f"(d[11]), "+f"(d[12]), "+f"(d[13]), "+f"(d[14]), "+f"(d[15]), "+f"(d[16]), "+f"(d[17]), "+f"(d[18]), "+f"(d[19]), "+f"(d[20]), "+f"(d[21]), "+f"(d[22]), "+f"(d[23]), "+f"(d[24]), "+f"(d[25]), "+f"(d[26]), "+f"(d[27]), "+f"(d[28]), "+f"(d[29]), "+f"(d[30]), "+f"(d[31]), "+f"(d[32]), "+f"(d[33]), "+f"(d[34]), "+f"(d[35]), "+f"(d[36]), "+f"(d[37]), "+f"(d[38]), "+f"(d[39]), "+f"(d[40]), "+f"(d[41]), "+f"(d[42]), "+f"(d[43]), "+f"(d[44]), "+f"(d[45]), "+f"(d[46]), "+f"(d[47]), "+f"(d[48]), "+f"(d[49]), "+f"(d[50]), "+f"(d[51]), "+f"(d[52]), "+f"(d[53]), "+f"(d[54]), "+f"(d[55]), "+f"(d[56]), "+f"(d[57]), "+f"(d[58]), "+f"(d[59]), "+f"(d[60]), "+f"(d[61]), "+f"(d[62]), "+f"(d[63])
    : "l"(da), "l"(db), "r"(scale_d));
}


constexpr float LOG2E = 1.4426950408889634f;

DEVINL uint32_t hadd2(uint32_t a, uint32_t b) { uint32_t r; asm("add.rn.bf16x2 %0, %1, %2;" : "=r"(r) : "r"(a), "r"(b)); return r; }
DEVINL uint32_t xw(uint32_t a, uint32_t b) { return __byte_perm(a, b, 0x5432); }
DEVINL void red_add(unsigned* p, unsigned v) { asm volatile("red.relaxed.gpu.global.add.u32 [%0], %1;" ::"l"(p), "r"(v) : "memory"); }
DEVINL void wait_cnt(const unsigned* p, unsigned target) {
  int it = 0;
#pragma unroll 1
  while ((int)(ld_relaxed(p) - target) < 0) {
    __nanosleep(64);
    if (++it > SPIN_LIMIT) break;
  }
  (void)ld_acquire(p);
}
DEVINL void sts64(uint32_t a, uint32_t x, uint32_t y) { asm volatile("st.shared.v2.b32 [%0], {%1,%2};" ::"r"(a), "r"(x), "r"(y) : "memory"); }
DEVINL uint2 lds64(uint32_t a) {
  uint2 v;
  asm volatile("ld.shared.v2.b32 {%0,%1}, [%2];" : "=r"(v.x), "=r"(v.y) : "r"(a) : "memory");
  return v;
}
DEVINL void mma16808(float (&c)[4], uint32_t a0, uint32_t a1, uint32_t b0) {
  asm volatile("mma.sync.aligned.m16n8k8.row.col.f32.bf16.bf16.f32 {%0,%1,%2,%3}, {%4,%5}, {%6}, {%0,%1,%2,%3};"
      : "+f"(c[0]), "+f"(c[1]), "+f"(c[2]), "+f"(c[3]) : "r"(a0), "r"(a1), "r"(b0));
}
DEVINL void ldsm_r(uint32_t* r, uint32_t addr) { ldsm_x4(r[0], r[1], r[2], r[3], addr); }
DEVINL void ldsm_tr(uint32_t* r, uint32_t addr) { ldsm_x4_t(r[0], r[1], r[2], r[3], addr); }
DEVINL void lds128_r(uint32_t* r, uint32_t a) { const uint4 v = lds128(a); r[0] = v.x; r[1] = v.y; r[2] = v.z; r[3] = v.w; }
DEVINL void tma_store_2d(const CUtensorMap* tm, uint32_t src, int c0, int c1) {
  asm volatile("cp.async.bulk.tensor.2d.global.shared::cta.bulk_group [%0, {%2, %3}], [%1];"
               ::"l"(tm), "r"(src), "r"(c0), "r"(c1) : "memory");
  asm volatile("cp.async.bulk.commit_group;" ::: "memory");
}

DEVINL void fence_async_global() { asm volatile("fence.proxy.async.global;" ::: "memory"); }

DEVINL int uch(int c) { return (c * 16) ^ ((c & 8) << 1); }
DEVINL void lda(uint32_t* r, uint32_t a) {
  asm volatile("ld.volatile.shared.b32 %0, [%4];\nld.volatile.shared.b32 %1, [%4+32];\nld.volatile.shared.b32 %2, [%4+-32];\nld.volatile.shared.b32 %3, [%4];"
               : "=r"(r[0]), "=r"(r[1]), "=r"(r[2]), "=r"(r[3]) : "r"(a) : "memory");
}
DEVINL void sts128_if(bool on, uint32_t a, uint32_t x, uint32_t y, uint32_t z, uint32_t w) {
  asm volatile("{\n.reg .pred q;\nsetp.ne.u32 q, %5, 0;\n@q st.shared.v4.b32 [%0], {%1,%2,%3,%4};\n}" ::"r"(a), "r"(x), "r"(y), "r"(z), "r"(w), "r"((uint32_t)on) : "memory");
}
DEVINL void red_v4(float4* p, float a, float b, float c) {
  asm volatile("red.relaxed.gpu.global.add.v4.f32 [%0], {%1, %2, %3, %4};" ::"l"(p), "f"(a), "f"(b), "f"(c), "f"(1.f) : "memory");
}
DEVINL unsigned short ldg16_now(const void* p) {
  unsigned short v;
  asm volatile("ld.global.nc.u16 %0, [%1];" : "=h"(v) : "l"(p));
  return v;
}
DEVINL uint32_t hmul2(uint32_t a, uint32_t b) { uint32_t r; asm("mul.rn.bf16x2 %0, %1, %2;" : "=r"(r) : "r"(a), "r"(b)); return r; }
DEVINL uint32_t hfma2(uint32_t a, uint32_t b, uint32_t c) { uint32_t r; asm("fma.rn.bf16x2 %0, %1, %2, %3;" : "=r"(r) : "r"(a), "r"(b), "r"(c)); return r; }
struct cplx { float re, im; };
DEVINL cplx cmul(cplx a, cplx b) { return {a.re * b.re - a.im * b.im, a.re * b.im + a.im * b.re}; }
DEVINL cplx csqr(cplx a) { return {a.re * a.re - a.im * a.im, (a.re + a.re) * a.im}; }
DEVINL cplx cexp_p(float ar2, float ang, float p) {
  const float m = ex2f(ar2 * p), th = ang * p;
  return {m * __cosf(th), m * __sinf(th)};
}

template <int LQ, int E, int K0, int K1>
DEVINL void conv_seg(float (&acc)[16][4], uint32_t (&R)[64], uint32_t arow) {
  constexpr int KST = 32 << LQ;
  ldsm_tr(&R[24], arow);
  ldsm_tr(&R[28], arow + KST);
  float tmp[4][4];
#pragma unroll
  for (int i = 0; i < 4; i++) { tmp[i][0] = tmp[i][1] = tmp[i][2] = tmp[i][3] = 0.f; }
#pragma unroll
  for (int k = K0; k <= K1; k++) {
    const int cur = 24 + 4 * ((k - K0) % 3), nxt = 24 + 4 * ((k - K0 + 2) % 3);
    if (k + 2 <= K1) ldsm_tr(&R[nxt], arow + (k + 2 - K0) * KST);
#pragma unroll
    for (int T = 0; T < 16; T++) {
      const int e = k - (8 >> LQ) * T + 16;
      if (e >= 0 && e < E) {
        if (LQ == 1 && (k & 1)) {
          mma16816(tmp[T & 3], R[cur], R[cur + 1], R[cur + 2], R[cur + 3], R[2 * e], R[2 * e + 1]);
          if (e == E - 1 || k + 1 >= K1) {
#pragma unroll
            for (int i = 0; i < 4; i++) { acc[T][i] += tmp[T & 3][i]; tmp[T & 3][i] = 0.f; }
          }
        } else {
          mma16816(acc[T], R[cur], R[cur + 1], R[cur + 2], R[cur + 3], R[2 * e], R[2 * e + 1]);
        }
      }
    }
  }
}
template <int E>
DEVINL void load_taps(uint32_t (&R)[64], uint32_t ta) {
#pragma unroll
  for (int e = 0; e < E; e++) { R[2 * e] = lds32(ta - e * 32); R[2 * e + 1] = lds32(ta - e * 32 - 16); }
}

__global__ void __launch_bounds__(512, 1)
fused_kernel(const __grid_constant__ CUtensorMap tm_x, const __grid_constant__ CUtensorMap tm_w,
             const __grid_constant__ CUtensorMap tm_wo,
             const __grid_constant__ CUtensorMap tm_out, const __grid_constant__ CUtensorMap tm_os,
             const __grid_constant__ CUtensorMap tm_ol, const __grid_constant__ CUtensorMap tm_xs,
             const __grid_constant__ CUtensorMap tm_xl, const __nv_bfloat16* __restrict__ x,
             const __nv_bfloat16* __restrict__ wphi,
             const __nv_bfloat16* __restrict__ logAr, const __nv_bfloat16* __restrict__ Aim,
             const __nv_bfloat16* __restrict__ Cre, const __nv_bfloat16* __restrict__ Cim,
             const __nv_bfloat16* __restrict__ logdt, const __nv_bfloat16* __restrict__ Dskip,
             const __nv_bfloat16* __restrict__ gatew) {
  extern __shared__ __align__(1024) unsigned char smem[];
  const uint32_t sb = smem_u32(smem);
  const int tid = threadIdx.x, warp = __shfl_sync(0xffffffffu, tid >> 5, 0), lane = tid & 31;
  const int wgi = __shfl_sync(0xffffffffu, tid >> 7, 0);
  const int g = lane >> 2, t = lane & 3;
  const int mi = lane >> 3, l7 = lane & 7;
  const int bid = blockIdx.x;
  const int hg_in = bid & 3, rt = (bid >> 2) & 15, hgblk = bid >> 6;
  const int hg = hgblk * 4 + hg_in;

  const uint32_t bar_full = sb + OFF_BAR;
  const uint32_t bar_empty = sb + OFF_BAR + 32;
  const uint32_t bar_full2 = sb + OFF_BAR + 64;
  const uint32_t bar_empty2 = sb + OFF_BAR + 128;
  const uint32_t bar_y = sb + OFF_BAR + 152;
  const uint32_t bar_vfree = sb + OFF_BAR + 160;
  const uint32_t bar_qfree = sb + OFF_BAR + 168;
  const uint32_t bar_aux = sb + OFF_BAR + 176;
  const uint32_t bar_ssm = sb + OFF_BAR + 184;
  const uint32_t bar_kv = sb + OFF_BAR + 192;
  const uint32_t bar_u = sb + OFF_BAR + 200;
  const uint32_t bar_mdone = sb + OFF_BAR + 208;
  const uint32_t bar_s0 = sb + OFF_BAR + 216;
  const uint32_t bar_xfree = sb + OFF_BAR + 224;
  const uint32_t bar_gw = sb + OFF_BAR + 232;
  const uint32_t bar_kg = sb + OFF_BAR + 240;
  const uint32_t bar_near = sb + OFF_BAR + 256;
  const uint32_t sm_epoch = sb + OFF_BAR + 384;


  if (wgi == 3) asm volatile("setmaxnreg.dec.sync.aligned.u32 64;");
  const int kch = hg * 64 + rt * 4 + (warp & 3);
  unsigned short q[16], rdt = 0;
  if (wgi == 2) {
    rdt = ldg16_now(logdt + kch);
#pragma unroll
    for (int i = 0; i < 4; i++) {
      const int n = kch * 128 + 32 * i + lane;
      q[4 * i] = ldg16_now(logAr + n); q[4 * i + 1] = ldg16_now(Aim + n);
      q[4 * i + 2] = ldg16_now(Cre + n); q[4 * i + 3] = ldg16_now(Cim + n);
    }
  }
  if (tid == 128) {
#pragma unroll
    for (int i = 0; i < 4; i++) mbar_init(bar_full + 8 * i, 1);
    asm volatile("fence.mbarrier_init.release.cluster;" ::: "memory");
#pragma unroll 1
    for (int st = 0; st < 4; st++) {
      const int k0 = (4 * hgblk + ((st + hg_in + 1) & 3)) * 64;
      const uint32_t dst = sb + OFF_RING + st * STAGE_BYTES;
      mbar_expect_tx(bar_full + 8 * st, STAGE_BYTES);
      tma_load_2d(dst, &tm_x, k0, rt * 128, bar_full + 8 * st);
      tma_load_2d(dst + 2 * BLK, &tm_w, hg * 64, k0, bar_full + 8 * st);
      tma_load_2d(dst + 3 * BLK, &tm_w, 512 + hg * 64, k0, bar_full + 8 * st);
      tma_load_2d(dst + 4 * BLK, &tm_w, 1024 + hg * 64, k0, bar_full + 8 * st);
    }
  }
  if (tid == 160) {
    constexpr unsigned long long c0 = 0x1111111188881111ull, c1 = 0x4422881341884414ull;
#pragma unroll
    for (int i = 4; i < 32; i++) mbar_init(sb + OFF_BAR + 8 * i, (int)(((i < 16 ? c0 : c1) >> (4 * (i & 15))) & 15));
    mbar_init(bar_near, 12);
    asm volatile("fence.mbarrier_init.release.cluster;" ::: "memory");
  }
  __syncwarp();
  if (wgi == 2) {
    asm volatile("bar.arrive 0, 512;" ::: "memory");
    asm volatile("setmaxnreg.inc.sync.aligned.u32 160;");
    const int w = warp - 8;
    const int ch = kch;
    const uint32_t park = sb + OFF_SSM + w * PARK;
    const uint32_t park2 = sb + 3 * BLK + w * PARK;
    const uint32_t tab = sb + OFF_TAB + w * 2048;
    const uint32_t ub = sb + OFF_U + w * UST + 512;
    const float dsk = bf_lo(__ldg((const unsigned short*)Dskip + ch));
    uint32_t W[56], R[64];
    float klast = 0.f, ka[5][4];
  auto kstore = [&](const uint32_t* V, uint32_t xb) {
    const uint32_t qa = xb + g * 512 + t * 16, ra = xb + 4096 + g * 256 + t * 8, sa = xb + 6144 + g * 128 + t * 4;
#pragma unroll
    for (int gg = 0; gg < 8; gg++) {
      sts128(qa + ((gg ^ (g & 1)) << 6), V[7 * gg], V[7 * gg + 1], V[7 * gg + 2], V[7 * gg + 3]);
      sts64(ra + ((gg ^ (g & 3)) << 5), V[7 * gg + 4], V[7 * gg + 5]);
      sts32(sa + ((gg ^ g) << 4), V[7 * gg + 6]);
    }
  };
    {
      uint32_t pa[4] = {0, 0, 0, 0}, pc[4] = {0, 0, 0, 0};
      float dt = 1.f;
#pragma unroll 1
      for (int u = 0; u < 4; u++) {
        if (u == 0) {
#pragma unroll
          for (int i = 0; i < 4; i++) { pa[i] = q[4 * i] | ((uint32_t)q[4 * i + 1] << 16); pc[i] = q[4 * i + 2] | ((uint32_t)q[4 * i + 3] << 16); }
          dt = bf_round(expf(bf_lo(rdt)));
        }
        if (u == 3) {
#pragma unroll
          for (int i = 0; i < 56; i++) R[i] = W[i];
        }
        const float fa = bf_lo(pa[0]), fi = bf_hi(pa[0]), fr = bf_lo(pc[0]), fc = bf_hi(pc[0]);
        pa[0] = pa[1]; pa[1] = pa[2]; pa[2] = pa[3]; pc[0] = pc[1]; pc[1] = pc[2]; pc[2] = pc[3];
        const float ar2 = -bf_round(expf(fa)) * dt * LOG2E;
        const float ang = fi * dt;
        const cplx C = {2.f * fr * dt, 2.f * fc * dt};
        const cplx w1 = cexp_p(ar2, ang, 1.f), W128 = cexp_p(ar2, ang, 128.f), m2b = cexp_p(ar2, ang, 244.f);
        const cplx E2 = csqr(w1), m2a = csqr(E2), m3a = csqr(m2a), E16 = csqr(m3a), m3b = cmul(m2b, m2a);
        const cplx W256 = csqr(W128), W512 = csqr(W256), W1024 = csqr(W512), W2048 = csqr(W1024);
        klast += C.re * W2048.re - C.im * W2048.im;
        cplx Al = {1.f, 0.f}, Be = C, S2 = cmul(C, W512), S3 = cmul(C, W1024);
        const uint32_t hc = pack2(W128.re, W128.re), hs = pack2(W128.im, -W128.im);
        const uint32_t oc = pack2(w1.re, w1.re), os2 = pack2(-w1.im, w1.im), bc = pack2(W256.re, W256.re), bs = pack2(-W256.im, W256.im);
#pragma unroll
        for (int gg = 0; gg < 8; gg++) {
          const uint32_t al = pack2(Al.re, -Al.im), be = pack2(Be.re, Be.im), bw = __byte_perm(be, 0, 0x1032);
          W[7 * gg] = al; W[7 * gg + 1] = hfma2(__byte_perm(al, 0, 0x1032), hs, hmul2(al, hc)); W[7 * gg + 2] = be;
          W[7 * gg + 3] = hfma2(bw, os2, hmul2(be, oc)); W[7 * gg + 4] = hfma2(bw, bs, hmul2(be, bc)); W[7 * gg + 5] = pack2(S2.re, S2.im);
          W[7 * gg + 6] = pack2(S3.re, S3.im);
          if (gg < 7) {
            Al = gg ? cmul(Al, E16) : E16;
            Be = cmul(Be, E2);
            S2 = cmul(S2, gg == 3 ? m2b : m2a);
            S3 = cmul(S3, (gg & 1) ? m3b : m3a);
          }
        }
        if (u < 2) kstore(W, park + (u & 1) * 7168);
      }
    }
    asm volatile("bar.sync 3, 160;" ::: "memory");
    mbar_wait(bar_mdone, 0);
    kstore(W, park2);
    kstore(R, park2 + 7168);
#pragma unroll
    for (int s = 0; s < 5; s++) { ka[s][0] = ka[s][1] = ka[s][2] = ka[s][3] = 0.f; }
    __syncwarp();
#pragma unroll 1
    for (int u = 0; u < 4; u++) {
      const uint32_t xb = (u < 2 ? park : park2) + (u & 1) * 7168;
#pragma unroll
      for (int km = 0; km < 8; km++) {
        lds128_r(&R[8 * km], xb + km * 512 + ((lane ^ ((km & 1) << 2)) << 4));
        const uint2 r2 = lds64(xb + 4096 + km * 256 + ((lane ^ ((km & 3) << 2)) << 3));
        R[8 * km + 4] = r2.x; R[8 * km + 5] = r2.y;
        R[8 * km + 6] = lds32(xb + 6144 + km * 128 + ((lane ^ (km << 2)) << 2));
      }
#pragma unroll
      for (int km = 0; km < 8; km++)
#pragma unroll
        for (int s = 0; s < 5; s++) mma16808(ka[s], R[8 * km], R[8 * km + 1], R[8 * km + 2 + s]);
    }
    __syncwarp();
    if (lane == 0) mbar_arrive(bar_kg);
#pragma unroll
    for (int o = 16; o > 0; o >>= 1) klast += __shfl_xor_sync(0xffffffffu, klast, o);
    mbar_wait(bar_gw, 0);
    {
        const uint32_t kw = park + 12160;
        {
          const float k512 = __shfl_sync(0xffffffffu, ka[3][0], 0), k1024 = __shfl_sync(0xffffffffu, ka[4][0], 0);
          if (lane == 0) ka[0][0] += dsk;
          if (lane == 31) ka[2][3] -= k512;
          float plo = __shfl_up_sync(0xffffffffu, ka[1][1], 1), phi = __shfl_up_sync(0xffffffffu, ka[1][3], 1);
          float nlo = __shfl_down_sync(0xffffffffu, ka[2][0], 1), nhi = __shfl_down_sync(0xffffffffu, ka[2][2], 1);
          const float l31 = __shfl_sync(0xffffffffu, ka[1][1], 31), h31 = __shfl_sync(0xffffffffu, ka[1][3], 31);
          const float e0 = __shfl_sync(0xffffffffu, ka[2][2], 0);
          if (lane == 0) { plo = 0.f; phi = l31; }
          if (lane == 31) { nlo = e0; nhi = 0.f; }
          sts128(kw + 64 + lane * 16, pack2(ka[0][0], plo), pack2(ka[1][0], ka[0][0]), pack2(ka[0][1], ka[1][0]), pack2(ka[1][1], ka[0][1]));
          sts128(kw + 576 + lane * 16, pack2(ka[0][2], phi), pack2(ka[1][2], ka[0][2]), pack2(ka[0][3], ka[1][2]), pack2(ka[1][3], ka[0][3]));
          sts128(kw + 1088 + lane * 16, pack2(ka[2][0], lane ? ka[2][0] : h31), pack2(ka[2][0], ka[2][0]), pack2(ka[2][1], ka[2][0]), pack2(nlo, ka[2][1]));
          sts128(kw + 1600 + lane * 16, pack2(ka[2][2], ka[2][2]), pack2(ka[2][2], ka[2][2]), pack2(ka[2][3], ka[2][2]), pack2(nhi, ka[2][3]));
          sts32(kw + (lane < 16 ? lane * 4 : (512 + lane) * 4), 0u);
          const int dd = lane - 16;
          sts32(tab + lane * 4, pack2((dd == -4 || dd == -3) ? -k1024 : 0.f, (dd == -3 || dd == -2) ? -k1024 : 0.f));
          sts32(tab + 128 + lane * 4, pack2((dd == 12 || dd == 13) ? -k1024 : 0.f, (dd == 13 || dd == 14) ? -k1024 : 0.f));
          sts32(tab + 256 + lane * 4, pack2(dd >= 12 ? klast : 0.f, dd >= 13 ? klast : 0.f));
          const uint32_t tw = tab + 512;
#pragma unroll
          for (int s = 0; s < 2; s++) { sts32(tw + s * 512 + lane * 4, 0u); sts32(tw + s * 512 + 384 + lane * 4, 0u); }
          const int i2 = 32 + 2 * g + (t & 1) + 32 * (t >> 1);
          sts32(tw + i2 * 4, pack2(ka[3][1], ka[3][0]));
          sts32(tw + (i2 + 16) * 4, pack2(ka[3][3], ka[3][2]));
          const int i3 = 32 + g + 16 * t;
          sts32(tw + 512 + i3 * 4, pack2(ka[4][1], ka[4][0]));
          sts32(tw + 512 + (i3 + 8) * 4, pack2(ka[4][3], ka[4][2]));
        }
        mbar_wait(bar_u, 0);
        __syncwarp();
#pragma unroll 1
        for (int it = 0; it < 4; it++) {
          uint4 cu[2], nx[2], pv[2];
#pragma unroll
          for (int j = 0; j < 2; j++) {
            const int ci = it * 32 + lane + 96 * j - 16;
            cu[j] = lds128(ub + uch(ci)); nx[j] = lds128(ub + uch(ci + 1)); pv[j] = lds128(ub + uch(ci - 1));
          }
#pragma unroll
          for (int j = 0; j < 2; j++) {
            const int li = it * 32 + lane + 96 * j;
            const uint4 c = cu[j], n = nx[j], v = pv[j];
            const uint32_t xm = xw(v.w, c.x), x0 = xw(c.x, c.y), x1 = xw(c.y, c.z), x2 = xw(c.z, c.w), x3 = xw(c.w, n.x), x4 = xw(n.x, n.y), x5 = xw(n.y, n.z);
            const uint32_t s0 = hadd2(hadd2(xm, x0), c.x), s1 = hadd2(hadd2(x0, x1), c.y), s2 = hadd2(hadd2(x1, x2), c.z), s3 = hadd2(hadd2(x2, x3), c.w);
            const bool lo = j ? li < 211 : it < 3, hi = j ? li < 147 : it < 3;
            sts128_if(lo, park + li * 16, s2, s3, hadd2(hadd2(x3, x4), n.x), hadd2(hadd2(x4, x5), n.y));
            const uint32_t f0 = hadd2(hadd2(v.w, c.y), s0), f1 = hadd2(hadd2(c.x, c.z), s1), f2 = hadd2(hadd2(c.y, c.w), s2), f3 = hadd2(hadd2(c.z, n.x), s3);
            sts128_if(lo, park + 3504 + li * 16, f0, f1, f2, f3);
            const uint32_t h0 = hadd2(hadd2(xw(v.z, v.w), x1), f0), h1 = hadd2(hadd2(xm, x2), f1), h2 = hadd2(hadd2(x0, x3), f2), h3 = hadd2(hadd2(x1, x4), f3);
            sts128_if(hi, park + 6912 + li * 16, h0, h1, h2, h3);
            sts128_if(hi, park + 9344 + li * 16, hadd2(hadd2(v.z, c.z), h0), hadd2(hadd2(v.w, c.w), h1), hadd2(hadd2(c.x, n.x), h2),
                      hadd2(hadd2(c.y, n.y), h3));
          }
        }
        float acc[16][4];
#pragma unroll
        for (int T = 0; T < 16; T++) { acc[T][0] = acc[T][1] = acc[T][2] = acc[T][3] = 0.f; }
        const int c2 = l7 + 8 * (mi >> 1);
        const int r16 = (mi & 1) * 16;
        load_taps<10>(R, tab + 512 + (2 * g + 95 - t) * 4);
        __syncwarp();
        conv_seg<2, 10, -1, 23>(acc, R, park + ((c2 & 1) ? 3504 + ((c2 + 1) >> 1) * 16 : (c2 >> 1) * 16) + 128 + r16);
        load_taps<9>(R, tab + 1024 + (g + 95 - t) * 4);
        conv_seg<3, 9, -1, 7>(acc, R, park + ((c2 & 1) ? 9344 : 6912) + (1 + c2) * 16 + r16);
        __syncwarp();
        {
          const int uc = 2 * (l7 + (lane >> 4) * 8) + (mi & 1);
          const uint32_t kaddr = kw + (16 + g - 2 * t) * 4, caddr = tab + (16 + g - 2 * t) * 4;
          int opq;
          asm volatile("mov.u32 %0, %%nsmid;" : "=r"(opq));
          uint32_t* S = &R[32];
#pragma unroll
          for (int j = 0; j < 5; j++) ldsm_r(&R[4 * j], ub + uch(uc - 14) + j * 512);
          lda(&S[16], caddr + 128);
          lda(&S[20], caddr + 256);
          lda(&S[24], kaddr + 2048);
          lda(&S[28], caddr);
#pragma unroll
          for (int T = 7; T < 16; T++) mma16816(acc[T], S[16], S[17], S[18], S[19], R[2 * T - 14], R[2 * T - 13]);
          mma16816(acc[15], S[20], S[21], S[22], S[23], R[0], R[1]);
#pragma unroll
          for (int j = 0; j < 8; j++) ldsm_r(&R[4 * j], ub + uch(uc) + j * 512);
#pragma unroll
          for (int j = 0; j < 4; j++) lda(&S[4 * j], kaddr + j * 512);
#pragma unroll
          for (int T = 4; T < 16; T++) mma16816(acc[T], S[24], S[25], S[26], S[27], R[2 * T - 8], R[2 * T - 7]);
#pragma unroll
          for (int T = 8; T < 16; T++) mma16816(acc[T], S[28], S[29], S[30], S[31], R[2 * T - 16], R[2 * T - 15]);
          __syncwarp();
          if (lane == 0) mbar_arrive(bar_near);
#pragma unroll 1
          for (int mp = 0; mp < 4; mp++) {
#pragma unroll
            for (int hb = 0; hb < 2; hb++) {
              const int ml = 2 * mp + hb;
              uint32_t* Sc = &S[16 * hb];
              uint32_t* Sn = &S[16 - 16 * hb];
              const uint32_t kp = kaddr + ml * 64 + 64;
              const uint32_t uo = ub + uch(uc - 2 * ml), un = ub + uch(uc - 2 * ml - 2);
              if (opq > 2 * hb) {
                if (hb || true) {
#pragma unroll
                  for (int j = 4; j < 8; j++) ldsm_r(&R[4 * j], uo + j * 512);
                }
#pragma unroll
                for (int j = 0; j < 4; j++) lda(&Sn[4 * j], kp + j * 512);
#pragma unroll
                for (int m = 0; m < 4; m++)
#pragma unroll
                  for (int T = m; T < 8; T++) mma16816(acc[T], Sc[4 * m], Sc[4 * m + 1], Sc[4 * m + 2], Sc[4 * m + 3], R[2 * (T - m)], R[2 * (T - m) + 1]);
              }
              if (opq > 2 * hb + 1) {
                ldsm_r(&R[0], un);
                ldsm_r(&R[4], un + 512);
#pragma unroll
                for (int m = 3; m >= 0; m--) {
#pragma unroll
                  for (int T = 8; T < 16; T++) mma16816(acc[T], Sc[4 * m], Sc[4 * m + 1], Sc[4 * m + 2], Sc[4 * m + 3], R[2 * (T - m)], R[2 * (T - m) + 1]);
                  if (m == 3) ldsm_r(&R[8], un + 2 * 512);
                  if (m == 1) ldsm_r(&R[12], un + 3 * 512);
                }
              }
            }
          }
        }
        __syncwarp();
        if (lane == 0) mbar_arrive(bar_ssm);
        {
          const uint32_t ya = park + 8192 + ((lane >> 4) * 128 + l7 * 16 + (mi & 1) * 8) * 2;
          const uint32_t tag = g == 0 ? 0x00010001u : 0u;
#pragma unroll
          for (int T = 0; T < 16; T += 2)
            stsm_x4_t(ya + T * 256, pack2(acc[T][0], acc[T][1]) | tag, pack2(acc[T][2], acc[T][3]) | tag,
                      pack2(acc[T + 1][0], acc[T + 1][1]) | tag, pack2(acc[T + 1][2], acc[T + 1][3]) | tag);
          mbar_wait(bar_empty2 + 8, 0);
          __syncwarp();
#pragma unroll
          for (int i = 0; i < 8; i++) lds128_r(&R[4 * i], park + 8192 + (i * 32 + lane) * 16);
#pragma unroll
          for (int i = 7; i >= 0; i--)
            st_relaxed_v4((uint4*)(g_yT + (size_t)ch * SEQ) + i * 32 + lane, R[4 * i], R[4 * i + 1], R[4 * i + 2], R[4 * i + 3]);
          uint4* src = (uint4*)(g_yT + (size_t)(hg_in * 128 + w * 32 + mi) * SEQ + rt * 128 + hgblk * 64) + l7;
          uint4 v[8];
#pragma unroll
          for (int i = 0; i < 8; i++) v[i].x = 0;
          __nanosleep(100);
#pragma unroll 1
          for (int it = 0; it < SPIN_LIMIT; it++) {
            uint32_t mn = 0xffffffffu;
#pragma unroll
            for (int i = 0; i < 8; i++)
              if (v[i].x == 0) v[i] = ld_relaxed_v4(src + i * (4 * SEQ / 8));
#pragma unroll
            for (int i = 0; i < 8; i++) mn = min(mn, v[i].x);
            if (mn != 0) break;
          }
          __syncwarp();
          mbar_wait(bar_empty2, 0);
#pragma unroll
          for (int i = 0; i < 8; i++) {
            const int c = w * 32 + i * 4 + mi;
            sts128(sb + 14 * BLK + c * 128 + ((l7 ^ (c & 7)) << 4), v[i].x, v[i].y, v[i].z, v[i].w);
          }
          __syncwarp();
          if (lane == 0) {
            mbar_arrive(bar_y);
          }
        }
    }
  } else if (wgi == 3) {
    if (warp == 12) asm volatile("bar.sync 0, 512;" ::: "memory");
    if (warp == 12) {
#pragma unroll 1
      for (int st = 0; st < 4; st++) {
        mbar_wait(bar_empty + 8 * st, 0);
        if (st == 3) mbar_wait(bar_xfree, 0);
        const int k0 = (4 + st - 4 * hgblk) * 64;
        const uint32_t dst = sb + OFF_RING + st * STAGE_BYTES;
        if (lane == 0) mbar_expect_tx(bar_full + 8 * st, STAGE_BYTES);
        __syncwarp();
        if (lane == 0) tma_load_2d(dst, &tm_x, k0, rt * 128, bar_full + 8 * st);
        else if (lane < 4) tma_load_2d(dst + (1 + lane) * BLK, &tm_w, (lane - 1) * 512 + hg * 64, k0, bar_full + 8 * st);
        __syncwarp();
      }
      mbar_wait(bar_aux, 0);
      {
        const unsigned target = (lds32(sm_epoch) & ~127u) + 128u;
        const uint32_t bar = bar_full2 + 8 * (lane & 7);
        const int cch = (lane + 4 * hgblk) & 7;
        const unsigned* flag = &g_ocnt[(rt * 2 + hgblk) * 8 + cch];
        if (lane < 8) mbar_expect_tx(bar, 3 * BLK);
        mbar_wait(bar_near, 0);
        if (lane < 8) {
          tma_load_2d(sb + w_off(lane, 0), &tm_wo, hg_in * 128, cch * 64, bar);
          tma_load_2d(sb + w_off(lane, 1), &tm_wo, hg_in * 128 + 64, cch * 64, bar);
        }
        __syncwarp();
        mbar_wait(bar_qfree, 0);
        bool need = lane < 8;
#pragma unroll 1
        for (int it = 0; it < SPIN_LIMIT; it++) {
          if (need && (int)(ld_relaxed(flag) - target) >= 0) {
            (void)ld_acquire(flag);
            fence_async_global();
            if (lane < 6) tma_load_2d(sb + o_off(lane), &tm_ol, cch * 64, rt * 128 + hgblk * 64, bar);
            need = false;
          }
          if (!__any_sync(0xffffffffu, need)) break;
          __nanosleep(60);
        }
        mbar_wait(bar_ssm, 0);
        if (lane == 6 || lane == 7) tma_load_2d(sb + o_off(lane), &tm_ol, cch * 64, rt * 128 + hgblk * 64, bar);
        if (lane == 0) red_add(&g_done, 1u);
      }
    } else {
      if (warp == 14) {
        const unsigned done = ld_relaxed(&g_done);
        asm volatile("bar.sync 0, 512;" ::: "memory");
        uint32_t w4[16];
#pragma unroll
        for (int i = 0; i < 16; i++) {
          const unsigned short* wb = (const unsigned short*)wphi + (hg * 4 + (i >> 2)) * 256 + 2 * t * 16 + g + (i & 1) * 128 + ((i >> 1) & 1) * 8;
          w4[i] = (uint32_t)__ldg(wb) | ((uint32_t)__ldg(wb + 16) << 16);
        }
#pragma unroll
        for (int h = 0; h < 4; h++) sts128(sb + OFF_WPHI + h * 512 + lane * 16, w4[4 * h], w4[4 * h + 1], w4[4 * h + 2], w4[4 * h + 3]);
        if (lane == 0) sts32(sm_epoch, done);
        __syncwarp();
        if (lane == 0) mbar_arrive(bar_aux);
        mbar_wait(bar_s0, 0);
#pragma unroll
        for (int i = 0; i < 4; i++) sts128(sb + OFF_U + i * UST + lane * 16, 0, 0, 0, 0);
        __syncwarp();
        if (lane == 0) {
          wait_cnt(&g_xcnt[hg * 32], (done & ~127u) + 128u);
          fence_async_global();
          mbar_expect_tx(bar_u, 16384);
#pragma unroll 1
          for (int i = 0; i < 4; i++) tma_load_2d(sb + OFF_U + i * UST + 512, &tm_xl, 0, (hg * 64 + rt * 4 + i) * 128, bar_u);
        }
        __syncwarp();
      } else {
        const int half = (warp - 13) >> 1;
        const int row0 = rt * 128 + hg * 16 + half * 8;
        const uint4* xr = (const uint4*)(x + (size_t)row0 * DM) + lane;
        float mine = 0.f;
        if (lane < 24) g_kva[hg * 768 + rt * 48 + half * 24 + lane] = make_float4(0.f, 0.f, 0.f, 0.f);
        asm volatile("bar.sync 0, 512;" ::: "memory");
        {
            mbar_wait(bar_full + 24, 0);
            const uint32_t stg = sb + OFF_TAB + half * 4096;
#pragma unroll 1
            for (int rd = 0; rd < 2; rd++) {
              const uint32_t src = sb + OFF_RING + 3 * STAGE_BYTES + (64 * half + 32 * rd + lane) * 128;
              uint32_t r[8][4];
#pragma unroll
              for (int cc = 0; cc < 8; cc++) ldsm_x4(r[cc][0], r[cc][1], r[cc][2], r[cc][3], src + ((cc ^ l7) << 4));
              if (rd == 1) {
                if (lane == 0) asm volatile("cp.async.bulk.wait_group.read 0;" ::: "memory");
                __syncwarp();
              }
#pragma unroll
              for (int cc = 0; cc < 8; cc++) stsm_x4_t(stg + (cc * 8 + l7) * 64 + ((mi ^ ((l7 >> 1) & 3)) << 4), r[cc][0], r[cc][1], r[cc][2], r[cc][3]);
              asm volatile("fence.proxy.async.shared::cta;" ::: "memory");
              __syncwarp();
              if (lane == 0) tma_store_2d(&tm_xs, stg, rt * 128 + 64 * half + 32 * rd, hg * 64);
            }
            if (lane == 0) mbar_arrive(bar_xfree);

            __threadfence();
            __syncwarp();
            if (lane == 0) {
              asm volatile("cp.async.bulk.wait_group 0;" ::: "memory");
              mbar_arrive(bar_gw);
              red_add(&g_xcnt[hg * 32], 4u);
            }
          }
#pragma unroll 1
        for (int b = 0; b < 2; b++) {
          const uint4 gw = __ldg((const uint4*)gatew + b * 32 + lane);
          uint4 a[8];
#pragma unroll
          for (int r = 0; r < 8; r++) a[r] = __ldg(xr + r * 64 + b * 32);
          float sr[8];
#pragma unroll
          for (int r = 0; r < 8; r++) {
            float s = bf_lo(a[r].x) * bf_lo(gw.x);
            s = fmaf(bf_hi(a[r].x), bf_hi(gw.x), s); s = fmaf(bf_lo(a[r].y), bf_lo(gw.y), s); s = fmaf(bf_hi(a[r].y), bf_hi(gw.y), s);
            s = fmaf(bf_lo(a[r].z), bf_lo(gw.z), s); s = fmaf(bf_hi(a[r].z), bf_hi(gw.z), s);
            s = fmaf(bf_lo(a[r].w), bf_lo(gw.w), s); sr[r] = fmaf(bf_hi(a[r].w), bf_hi(gw.w), s);
          }
#pragma unroll
          for (int i = 0; i < 4; i++) sr[i] = ((lane & 16) ? sr[i + 4] : sr[i]) + __shfl_xor_sync(0xffffffffu, (lane & 16) ? sr[i] : sr[i + 4], 16);
#pragma unroll
          for (int i = 0; i < 2; i++) sr[i] = ((lane & 8) ? sr[i + 2] : sr[i]) + __shfl_xor_sync(0xffffffffu, (lane & 8) ? sr[i] : sr[i + 2], 8);
          mine += ((lane & 4) ? sr[1] : sr[0]) + __shfl_xor_sync(0xffffffffu, (lane & 4) ? sr[0] : sr[1], 4);
        }
        mine += __shfl_xor_sync(0xffffffffu, mine, 1);
        mine += __shfl_xor_sync(0xffffffffu, mine, 2);
        if (t == 0) g_gate[row0 + g] = 1.f / (1.f + __expf(-mine));
        {
          uint4* yz = (uint4*)(g_yT + (size_t)(hg_in * 128 + half * 64 + mi) * SEQ + rt * 128 + hgblk * 64) + l7;
#pragma unroll 4
          for (int i = 0; i < 16; i++) yz[i * (4 * SEQ / 8)] = make_uint4(0, 0, 0, 0);
        }
        __threadfence();
        __syncwarp();
        if (lane == 0) red_add(&g_xcnt[(8 + half) * 32], 1u);
      }
      const int idx = (warp - 13) * 32 + lane;
      mbar_wait(bar_vfree, 0);
      {
        const float4* src = g_kva + hg * 768 + idx;
        const bool three = idx < 64;
        uint4 v[9];
#pragma unroll 1
        for (int it = 0; it < SPIN_LIMIT; it++) {
          bool ok = true;
#pragma unroll
          for (int i = 0; i < 9; i++)
            if (i < 6 || three) v[i] = ld_relaxed_v4(src + (i / 3) * 96 + (i % 3) * 256);
#pragma unroll
          for (int i = 0; i < 9; i++)
            if (i < 6 || three) ok = ok && v[i].w == 0x41800000u;
          if (ok) break;
          __nanosleep(100);
        }
        mbar_wait(bar_kg, 0);
#pragma unroll
        for (int r = 0; r < 3; r++) {
          if (r < 2 || three) {
            const int i = idx + 96 * r;
            const uint4 a = v[3 * r], b = v[3 * r + 1], c = v[3 * r + 2];
            sts128(sb + OFF_KV + i * 16, pack2(__uint_as_float(a.x), __uint_as_float(a.y)), pack2(__uint_as_float(a.z), __uint_as_float(b.x)),
                   pack2(__uint_as_float(b.y), __uint_as_float(b.z)), pack2(__uint_as_float(c.x), __uint_as_float(c.y)));
            if (g < 4) sts16(sb + OFF_KV + 4096 + (i >> 5) * 32 + t * 8 + g * 2, (uint16_t)pack2(__uint_as_float(c.z), 0.f));
          }
        }
        __syncwarp();
        if (lane == 0) mbar_arrive(bar_kv);
      }
      if (tid == 448) {
        const unsigned target = (lds32(sm_epoch) & ~127u) + 128u;
        wait_cnt(&g_xcnt[8 * 32], target);
        wait_cnt(&g_xcnt[9 * 32], target);
        mbar_arrive(bar_empty2 + 8);
      }
    }
  } else {
    if (warp == 5) asm volatile("bar.arrive 3, 160;" ::: "memory");
    asm volatile("bar.sync 0, 512;" ::: "memory");
    asm volatile("setmaxnreg.inc.sync.aligned.u32 144;");
    const int wg = wgi, wq = warp & 3;
    const int srow = warp * 16 + l7 + (mi & 1) * 8;
    const int hi16 = lane >> 4;
    const uint32_t ONE = 0x3F803F80u;
    uint32_t kq[8][4];
    {
      float d[96];
#pragma unroll 1
      for (int kc = 0; kc < 8; kc++) {
        const int st = kc & 3;
        mbar_wait(bar_full + 8 * st, kc >> 2);
        const uint32_t sa = sb + OFF_RING + st * STAGE_BYTES + wg * BLK;
        const uint32_t sw = sb + OFF_RING + st * STAGE_BYTES + 2 * BLK;
        wg_fence();
#pragma unroll
        for (int k = 0; k < 4; k++)
          wgmma_ss_n192(d, make_desc(sa + k * 32, 16, 1024), make_desc(sw + k * 2048, BLK, 1024), (kc | k) != 0);
        wg_commit();
        if (kc > 0) {
          wg_wait<1>();
          if (lane == 0) {
            mbar_arrive(bar_empty + 8 * ((kc - 1) & 3));
            if (kc == 5) mbar_arrive(bar_s0);
          }
        }
      }
      wg_wait<0>();
      if (lane == 0) mbar_arrive(bar_mdone);
#pragma unroll
      for (int h = 0; h < 4; h++)
#pragma unroll
        for (int i = 0; i < 4; i++) {
          kq[h][i] = pack2(d[32 + 8 * h + 2 * i], d[33 + 8 * h + 2 * i]);
          kq[4 + h][i] = pack2(d[8 * h + 2 * i], d[8 * h + 2 * i + 1]);
        }
      mbar_wait(bar_mdone, 0);
#pragma unroll
      for (int h = 0; h < 4; h++) {
        const int jv = 64 + 8 * h;
        stsm_x4(sb + OFF_VST + srow * 128 + (((2 * h + hi16) ^ l7) << 4), pack2(d[jv], d[jv + 1]), pack2(d[jv + 2], d[jv + 3]),
                pack2(d[jv + 4], d[jv + 5]), pack2(d[jv + 6], d[jv + 7]));
      }
    }
    mbar_wait(bar_aux, 0);
#pragma unroll 1
    for (int it = 0; it < 2; it++) {
      float ep[4][2][4], en[4][2][4];
      uint32_t lg[4][4];
      float pmin = 1.f;
      {
        uint4 wp[4];
        float c0[4][4], c1[4][4];
#pragma unroll
        for (int j = 0; j < 4; j++) wp[j] = lds128(sb + OFF_WPHI + j * 512 + lane * 16);
#pragma unroll
        for (int j = 0; j < 4; j++) {
#pragma unroll
          for (int i = 0; i < 4; i++) { c0[j][i] = 0.f; c1[j][i] = 0.f; }
          mma16816(c0[j], kq[j][0], kq[j][1], kq[j][2], kq[j][3], wp[j].x, wp[j].y);
          mma16816(c1[j], kq[j][0], kq[j][1], kq[j][2], kq[j][3], wp[j].z, wp[j].w);
        }
#pragma unroll
        for (int j = 0; j < 4; j++) {
          lg[j][0] = pack2(c0[j][0], c0[j][1]); lg[j][1] = pack2(c1[j][0], c1[j][1]);
          lg[j][2] = pack2(c0[j][2], c0[j][3]); lg[j][3] = pack2(c1[j][2], c1[j][3]);
        }
      }
#pragma unroll
      for (int j = 0; j < 4; j++) {
        const uint32_t ma = hmax2(lg[j][0], lg[j][1]), mb = hmax2(lg[j][2], lg[j][3]);
        uint32_t m = hmax2(__byte_perm(ma, mb, 0x5410), __byte_perm(ma, mb, 0x7632));
        m = hmax2(m, __shfl_xor_sync(0xffffffffu, m, 1));
        m = hmax2(m, __shfl_xor_sync(0xffffffffu, m, 2));
#pragma unroll
        for (int r = 0; r < 2; r++) {
          const float ml = -(r ? bf_hi(m) : bf_lo(m)) * LOG2E;
          float* e = ep[j][r];
          e[0] = ex2f(fmaf(bf_lo(lg[j][2 * r]), LOG2E, ml)); e[1] = ex2f(fmaf(bf_hi(lg[j][2 * r]), LOG2E, ml));
          e[2] = ex2f(fmaf(bf_lo(lg[j][2 * r + 1]), LOG2E, ml)); e[3] = ex2f(fmaf(bf_hi(lg[j][2 * r + 1]), LOG2E, ml));
          const float s01 = e[0] * e[1], s23 = e[2] * e[3], pr = s01 * s23, rr = rcpf(pr);
          const float i01 = rr * s23, i23 = rr * s01;
          en[j][r][0] = i01 * e[1]; en[j][r][1] = i01 * e[0]; en[j][r][2] = i23 * e[3]; en[j][r][3] = i23 * e[2];
          pmin = fminf(pmin, pr);
        }
      }
      if (__any_sync(0xffffffffu, !(pmin >= 7.9e-31f))) {
#pragma unroll
        for (int j = 0; j < 4; j++) {
          const uint32_t ma = hmin2(lg[j][0], lg[j][1]), mb = hmin2(lg[j][2], lg[j][3]);
          uint32_t m = hmin2(__byte_perm(ma, mb, 0x5410), __byte_perm(ma, mb, 0x7632));
          m = hmin2(m, __shfl_xor_sync(0xffffffffu, m, 1));
          m = hmin2(m, __shfl_xor_sync(0xffffffffu, m, 2));
#pragma unroll
          for (int r = 0; r < 2; r++) {
            const float ml = (r ? bf_hi(m) : bf_lo(m)) * LOG2E;
            en[j][r][0] = ex2f(fmaf(bf_lo(lg[j][2 * r]), -LOG2E, ml)); en[j][r][1] = ex2f(fmaf(bf_hi(lg[j][2 * r]), -LOG2E, ml));
            en[j][r][2] = ex2f(fmaf(bf_lo(lg[j][2 * r + 1]), -LOG2E, ml)); en[j][r][3] = ex2f(fmaf(bf_hi(lg[j][2 * r + 1]), -LOG2E, ml));
          }
        }
      }
      const uint32_t prow = sb + OFF_PHK + srow * 256;
      uint32_t Pk[4][4], Nk[4][4];
#pragma unroll
      for (int j = 0; j < 4; j++) {
        Pk[j][0] = pack2(ep[j][0][0], ep[j][0][1]); Pk[j][1] = pack2(ep[j][1][0], ep[j][1][1]);
        Pk[j][2] = pack2(ep[j][0][2], ep[j][0][3]); Pk[j][3] = pack2(ep[j][1][2], ep[j][1][3]);
        Nk[j][0] = pack2(en[j][0][0], en[j][0][1]); Nk[j][1] = pack2(en[j][1][0], en[j][1][1]);
        Nk[j][2] = pack2(en[j][0][2], en[j][0][3]); Nk[j][3] = pack2(en[j][1][2], en[j][1][3]);
      }
      if (it == 0) {
        float spa[4][4], sna[4][4];
#pragma unroll
        for (int j = 0; j < 4; j++) {
#pragma unroll
          for (int i = 0; i < 4; i++) { spa[j][i] = 0.f; sna[j][i] = 0.f; }
          mma16816(spa[j], Pk[j][0], Pk[j][1], Pk[j][2], Pk[j][3], ONE, ONE);
          mma16816(sna[j], Nk[j][0], Nk[j][1], Nk[j][2], Nk[j][3], ONE, ONE);
        }
#pragma unroll
        for (int j = 0; j < 4; j++) {
          const float r0 = rcpf(spa[j][0] * sna[j][0]), r1 = rcpf(spa[j][2] * sna[j][2]);
          const uint32_t c0 = pack2(r0 * sna[j][0], r0 * spa[j][0]), c1 = pack2(r1 * sna[j][2], r1 * spa[j][2]);
          const uint32_t p0 = __byte_perm(c0, 0, 0x1010), n0 = __byte_perm(c0, 0, 0x3232), p1 = __byte_perm(c1, 0, 0x1010), n1 = __byte_perm(c1, 0, 0x3232);
          Pk[j][0] = hmul2(Pk[j][0], p0); Pk[j][1] = hmul2(Pk[j][1], p1); Pk[j][2] = hmul2(Pk[j][2], p0); Pk[j][3] = hmul2(Pk[j][3], p1);
          Nk[j][0] = hmul2(Nk[j][0], n0); Nk[j][1] = hmul2(Nk[j][1], n1); Nk[j][2] = hmul2(Nk[j][2], n0); Nk[j][3] = hmul2(Nk[j][3], n1);
          stsm_x4(prow + (((4 * j + hi16) ^ l7) << 4), Pk[j][0], Pk[j][1], Pk[j][2], Pk[j][3]);
          stsm_x4(prow + (((4 * j + 2 + hi16) ^ l7) << 4), Nk[j][0], Nk[j][1], Nk[j][2], Nk[j][3]);
        }
#pragma unroll
        for (int i = 0; i < 16; i++) kq[i >> 2][i & 3] = kq[(i >> 2) + 4][i & 3];
      } else {
#pragma unroll
        for (int i = 0; i < 16; i++) { kq[i >> 2][i & 3] = Pk[i >> 2][i & 3]; kq[4 + (i >> 2)][i & 3] = Nk[i >> 2][i & 3]; }
      }
      if (it == 0) {
        named_bar(1, 256);
        const int hh = warp >> 1, ks = warp & 1;
        float D[2][4][4];
#pragma unroll
        for (int i = 0; i < 8; i++) { D[i >> 2][i & 3][0] = D[i >> 2][i & 3][1] = D[i >> 2][i & 3][2] = D[i >> 2][i & 3][3] = 0.f; }
        const uint32_t va = sb + OFF_VST + (l7 + (mi >> 1) * 8) * 128 + (((2 * hh + (mi & 1)) ^ l7) << 4);
        const uint32_t pa = sb + OFF_PHK + (l7 + (mi & 1) * 8) * 256 + (((4 * hh + 2 * ks + (mi >> 1)) ^ l7) << 4);
        uint32_t A[8][4], B[8][4];
#pragma unroll
        for (int s = 0; s < 8; s++) {
          ldsm_x4_t(A[s][0], A[s][1], A[s][2], A[s][3], va + s * 16 * 128);
          ldsm_x4_t(B[s][0], B[s][1], B[s][2], B[s][3], pa + s * 16 * 256);
        }
#pragma unroll
        for (int s = 0; s < 8; s++) {
          mma16816(D[s & 1][0], A[s][0], A[s][1], A[s][2], A[s][3], B[s][0], B[s][1]);
          mma16816(D[s & 1][1], A[s][0], A[s][1], A[s][2], A[s][3], B[s][2], B[s][3]);
          if (s & 1) {
            mma16816(D[(s >> 1) & 1][2], ONE, ONE, ONE, ONE, hadd2(B[s][0], B[s - 1][0]), hadd2(B[s][1], B[s - 1][1]));
            mma16816(D[(s >> 1) & 1][3], ONE, ONE, ONE, ONE, hadd2(B[s][2], B[s - 1][2]), hadd2(B[s][3], B[s - 1][3]));
          }
        }
        const float zz = (g & 2) ? ((g & 1) ? D[0][3][1] + D[1][3][1] : D[0][3][0] + D[1][3][0])
                                 : ((g & 1) ? D[0][2][1] + D[1][2][1] : D[0][2][0] + D[1][2][0]);
        float4* kp = g_kva + hg * 768 + tid;
        mbar_wait(bar_u, 0);
        red_v4(kp, D[0][0][0] + D[1][0][0], D[0][0][1] + D[1][0][1], D[0][1][0] + D[1][1][0]);
        red_v4(kp + 256, D[0][1][1] + D[1][1][1], D[0][0][2] + D[1][0][2], D[0][0][3] + D[1][0][3]);
        red_v4(kp + 512, D[0][1][2] + D[1][1][2], D[0][1][3] + D[1][1][3], zz);
        __syncwarp();
        if (lane == 0) { mbar_arrive(bar_vfree); mbar_arrive(bar_near); }
      }
    }
    const int row0 = rt * 128 + hgblk * 64 + wq * 16 + g;
    uint32_t gv0 = 0, gv1 = 0;
    const uint32_t os = sb + OFF_PHQ + warp * 2048;
    {
      uint32_t ow[4][4];
      mbar_wait(bar_kv, 0);
      uint4 kP[4], kN[4];
      uint2 zP[4], zN[4];
#pragma unroll
      for (int h = 0; h < 4; h++) {
        zP[h] = lds64(sb + OFF_KV + 4096 + h * 64 + t * 8); zN[h] = lds64(sb + OFF_KV + 4096 + h * 64 + 32 + t * 8);
        kP[h] = lds128(sb + OFF_KV + h * 1024 + lane * 16);
        kN[h] = lds128(sb + OFF_KV + h * 1024 + 512 + lane * 16);
      }
#pragma unroll
      for (int h = 0; h < 4; h++) {
        float P0[4] = {0.f, 0.f, 0.f, 0.f}, P1[4] = {0.f, 0.f, 0.f, 0.f}, PZ[4] = {0.f, 0.f, 0.f, 0.f};
        float N0[4] = {0.f, 0.f, 0.f, 0.f}, N1[4] = {0.f, 0.f, 0.f, 0.f}, NZ[4] = {0.f, 0.f, 0.f, 0.f};
        mma16816(PZ, kq[h][0], kq[h][1], kq[h][2], kq[h][3], (g & 1) ? ONE : zP[h].x, (g & 1) ? ONE : zP[h].y);
        mma16816(NZ, kq[4 + h][0], kq[4 + h][1], kq[4 + h][2], kq[4 + h][3], (g & 1) ? ONE : zN[h].x, (g & 1) ? ONE : zN[h].y);
        mma16816(P0, kq[h][0], kq[h][1], kq[h][2], kq[h][3], kP[h].x, kP[h].y);
        mma16816(P1, kq[h][0], kq[h][1], kq[h][2], kq[h][3], kP[h].z, kP[h].w);
        mma16816(N0, kq[4 + h][0], kq[4 + h][1], kq[4 + h][2], kq[4 + h][3], kN[h].x, kN[h].y);
        mma16816(N1, kq[4 + h][0], kq[4 + h][1], kq[4 + h][2], kq[4 + h][3], kN[h].z, kN[h].w);
#pragma unroll
        for (int r = 0; r < 2; r++) {
          const float rn = rcpf(NZ[2 * r + 1]), sp = PZ[2 * r + 1] * rn;
          const float id = rcpf(fmaf(NZ[2 * r], sp, fmaf(1e-6f, PZ[2 * r + 1], PZ[2 * r])));
          const float fN = sp * id;
          ow[h][r] = pack2(fmaf(P0[2 * r], id, N0[2 * r] * fN), fmaf(P0[2 * r + 1], id, N0[2 * r + 1] * fN));
          ow[h][2 + r] = pack2(fmaf(P1[2 * r], id, N1[2 * r] * fN), fmaf(P1[2 * r + 1], id, N1[2 * r + 1] * fN));
        }
      }
#pragma unroll
      for (int h = 0; h < 4; h++)
        stsm_x4(os + (l7 + (mi & 1) * 8) * 128 + (((2 * h + hi16) ^ l7) << 4), ow[h][0], ow[h][1], ow[h][2], ow[h][3]);
      asm volatile("fence.proxy.async.shared::cta;" ::: "memory");
      __syncwarp();
      if (lane == 0) {
        tma_store_2d(&tm_os, os, hg * 64, rt * 128 + warp * 16);
        asm volatile("cp.async.bulk.wait_group 0;" ::: "memory");
        if (wg == 0) mbar_arrive(bar_qfree);
        fence_async_global();
        red_add(&g_ocnt[(rt * 2 + wg) * 8 + hg], 32u);
      }
      __syncwarp();
    }
    {
    float acc[64];
    if (wg == 0) {
      mbar_wait(bar_full2 + 24, 0);
      gv0 = ld_relaxed(&g_gate[row0]); gv1 = ld_relaxed(&g_gate[row0 + 8]);
    }
#pragma unroll 1
    for (int i = 8 * wg; i < 8; i++) {
      if (i == 1) mbar_wait(bar_ssm, 0);
      mbar_wait(bar_full2 + 8 * i, 0);
      const uint32_t sa = sb + o_off(i), sw = sb + w_off(i, 0), lbo = i < 6 ? BLK : PARK;
      wg_fence();
#pragma unroll
      for (int k = 0; k < 4; k++) wgmma_ss_n128(acc, make_desc(sa + k * 32, 16, 1024), make_desc(sw + k * 2048, lbo, 1024), (i | k) != 0);
      wg_commit();
      if (i == 0) {
        wg_wait<0>();
        if (lane == 0) mbar_arrive(bar_empty2);
      }
    }
    {
      const float g0 = __uint_as_float(gv0), g1 = __uint_as_float(gv1);
      const uint32_t h0 = pack2(1.f - g0, 1.f - g0), h1 = pack2(1.f - g1, 1.f - g1);
      wg_wait<0>();
      if (wg == 0) named_bar(2, 128);
      uint32_t ga[32];
#pragma unroll
      for (int j = 0; j < 32; j++) ga[j] = (j & 1) ? pack2(g1 * acc[2 * j], g1 * acc[2 * j + 1]) : pack2(g0 * acc[2 * j], g0 * acc[2 * j + 1]);
      const uint32_t ya = sb + 14 * BLK + ((mi >> 1) * 8 + l7) * 128 + (((2 * wq + (mi & 1)) ^ l7) << 4);
      const uint32_t ob = wg ? os : sb + 4 * BLK + wq * 2048;
      const uint32_t oa = ob + (l7 + (mi & 1) * 8) * 128;
      if (wg == 0) mbar_wait(bar_y, 0);
      uint32_t y[8][4];
#pragma unroll
      for (int np = 0; np < 8; np++) ldsm_x4_t(y[np][0], y[np][1], y[np][2], y[np][3], ya + np * 16 * 128);
#pragma unroll
      for (int np = 0; np < 8; np++)
        stsm_x4(oa + (wg ? 0 : (np >> 2) * BLK) + (((2 * (np & 3) + hi16) ^ l7) << 4), hfma2(h0, y[np][0], ga[4 * np]), hfma2(h1, y[np][1], ga[4 * np + 1]),
                hfma2(h0, y[np][2], ga[4 * np + 2]), hfma2(h1, y[np][3], ga[4 * np + 3]));
      asm volatile("fence.proxy.async.shared::cta;" ::: "memory");
      __syncwarp();
      if (lane == 0 && wg == 1) mbar_arrive(bar_qfree);
      if (lane == 0 && wg == 0) {
        tma_store_2d(&tm_out, ob, hg_in * 128, rt * 128 + hgblk * 64 + wq * 16);
        tma_store_2d(&tm_out, ob + BLK, hg_in * 128 + 64, rt * 128 + hgblk * 64 + wq * 16);
        asm volatile("cp.async.bulk.wait_group.read 0;" ::: "memory");
      }
    }
    }
  }
}

typedef CUresult (*EncodeFn)(CUtensorMap*, CUtensorMapDataType, cuuint32_t, void*, const cuuint64_t*, const cuuint64_t*,
                             const cuuint32_t*, const cuuint32_t*, CUtensorMapInterleave, CUtensorMapSwizzle,
                             CUtensorMapL2promotion, CUtensorMapFloatOOBfill);

void make_map(EncodeFn fn, CUtensorMap* m, const void* p, uint64_t cols, uint64_t rows, uint32_t bc, uint32_t br,
              CUtensorMapSwizzle sw = CU_TENSOR_MAP_SWIZZLE_128B) {
  cuuint64_t dims[2] = {cols, rows};
  cuuint64_t strides[1] = {cols * 2};
  cuuint32_t box[2] = {bc, br};
  cuuint32_t es[2] = {1, 1};
  fn(m, CU_TENSOR_MAP_DATA_TYPE_BFLOAT16, 2, const_cast<void*>(p), dims, strides, box, es, CU_TENSOR_MAP_INTERLEAVE_NONE,
     sw, CU_TENSOR_MAP_L2_PROMOTION_L2_128B, CU_TENSOR_MAP_FLOAT_OOB_FILL_NONE);
}

}

extern "C" void kernel_launch(void* const* d_in, const int* in_sizes, int n_in, void* d_out, int out_size) {
  (void)in_sizes; (void)n_in; (void)out_size;
  static EncodeFn fn = nullptr;
  static void* optr = nullptr;
  static void* xptr = nullptr;
  if (!fn) {
    void* p = nullptr;
    cudaDriverEntryPointQueryResult st;
    cudaGetDriverEntryPoint("cuTensorMapEncodeTiled", &p, cudaEnableDefault, &st);
    fn = (EncodeFn)p;
    cudaGetSymbolAddress(&optr, g_o);
    cudaGetSymbolAddress(&xptr, g_xT);
    cudaFuncSetAttribute(fused_kernel, cudaFuncAttributeMaxDynamicSharedMemorySize, SMEM_BYTES);
  }
  typedef const __nv_bfloat16* bp;
  CUtensorMap tx, tw, two, to, tos, tol, txs, txl;
  make_map(fn, &tx, d_in[0], 512, 2048, 64, 128);
  make_map(fn, &tw, d_in[1], 1536, 512, 64, 64);
  make_map(fn, &two, d_in[3], 512, 512, 64, 64);
  make_map(fn, &to, d_out, 512, 2048, 64, 16);
  make_map(fn, &tos, optr, 512, 2048, 64, 16);
  make_map(fn, &tol, optr, 512, 2048, 64, 64);
  make_map(fn, &txs, xptr, 2048, 512, 32, 64, CU_TENSOR_MAP_SWIZZLE_64B);
  make_map(fn, &txl, xptr, 16, 65536, 16, 128, CU_TENSOR_MAP_SWIZZLE_32B);
  fused_kernel<<<NCTA, 512, SMEM_BYTES, cudaStreamPerThread>>>(
      tx, tw, two, to, tos, tol, txs, txl, (bp)d_in[0], (bp)d_in[2], (bp)d_in[5], (bp)d_in[6], (bp)d_in[7], (bp)d_in[8], (bp)d_in[9],
      (bp)d_in[10], (bp)d_in[11]);
}
```

```cpp
#include <cuda_runtime.h>
#include <cuda_bf16.h>
#include <cuda.h>
#include <stdint.h>

#define DEVINL __device__ __forceinline__

namespace {

constexpr int SEQ = 2048;
constexpr int DM = 512;
constexpr int NCTA = 128;

__device__ float4 g_kva[8 * 768];
__device__ float g_gate[SEQ];
__device__ __align__(1024) __nv_bfloat16 g_o[SEQ * DM];
__device__ __align__(1024) __nv_bfloat16 g_yT[DM * SEQ];
__device__ __align__(1024) __nv_bfloat16 g_xT[DM * SEQ];
__device__ unsigned g_done;
__device__ unsigned g_xcnt[10 * 32];
__device__ unsigned g_ocnt[16 * 2 * 8];

constexpr int BLK = 8192;
constexpr int STAGE_BYTES = 5 * BLK;
constexpr int OFF_RING = 0;
constexpr int OFF_U = 0;
constexpr int UST = 4608;
constexpr int OFF_KV = 3 * BLK;
constexpr int OFF_PHQ = 10 * BLK;
constexpr int OFF_VST = 14 * BLK;
constexpr int OFF_PHK = 16 * BLK;
constexpr int OFF_SSM = 20 * BLK;
constexpr int PARK = 14336;
constexpr int OFF_TAB = OFF_SSM + 4 * PARK;
constexpr int OFF_WPHI = OFF_TAB + 4 * 2048;
constexpr int OFF_BAR = OFF_WPHI + 2048;
constexpr int SMEM_BYTES = OFF_BAR + 512;
static_assert(SMEM_BYTES <= 232448, "smem");
DEVINL int o_off(int i) { return i == 5 ? OFF_TAB : ((0x1003BADC >> (4 * i)) & 15) * BLK; }
DEVINL int w_off(int i, int c) {
  return i < 6 ? (((0x432987 >> (4 * i)) & 15) * 2 + c) * BLK : OFF_SSM + ((i - 6) * 2 + c) * PARK;
}

constexpr int SPIN_LIMIT = 1 << 17;

DEVINL uint32_t smem_u32(const void* p) { return (uint32_t)__cvta_generic_to_shared(p); }
DEVINL void mbar_init(uint32_t bar, int cnt) { asm volatile("mbarrier.init.shared::cta.b64 [%0], %1;" ::"r"(bar), "r"(cnt)); }
DEVINL void mbar_expect_tx(uint32_t bar, uint32_t bytes) {
  asm volatile("mbarrier.arrive.expect_tx.shared::cta.b64 _, [%0], %1;" ::"r"(bar), "r"(bytes) : "memory");
}
DEVINL void mbar_arrive(uint32_t bar) { asm volatile("mbarrier.arrive.shared::cta.b64 _, [%0];" ::"r"(bar) : "memory"); }
DEVINL void mbar_wait(uint32_t bar, uint32_t parity) {
  uint32_t ok;
  int it = 0;
  do {
    asm volatile(
        "{\n.reg .pred p;\nmbarrier.try_wait.parity.shared::cta.b64 p, [%1], %2;\nselp.u32 %0, 1, 0, p;\n}\n"
        : "=r"(ok)
        : "r"(bar), "r"(parity)
        : "memory");
    if (++it > SPIN_LIMIT) break;
  } while (!ok);
}
DEVINL void tma_load_2d(uint32_t dst, const CUtensorMap* tm, int c0, int c1, uint32_t bar) {
  asm volatile(
      "cp.async.bulk.tensor.2d.shared::cluster.global.mbarrier::complete_tx::bytes [%0], [%1, {%3, %4}], [%2];"
      ::"r"(dst), "l"(tm), "r"(bar), "r"(c0), "r"(c1)
      : "memory");
}
DEVINL void named_bar(int id, int n) { asm volatile("bar.sync %0, %1;" ::"r"(id), "r"(n) : "memory"); }
DEVINL void wg_fence() { asm volatile("wgmma.fence.sync.aligned;" ::: "memory"); }
DEVINL void wg_commit() { asm volatile("wgmma.commit_group.sync.aligned;" ::: "memory"); }
template <int N>
DEVINL void wg_wait() { asm volatile("wgmma.wait_group.sync.aligned %0;" ::"n"(N) : "memory"); }
DEVINL uint64_t make_desc(uint32_t addr, uint32_t lbo, uint32_t sbo) {
  return (uint64_t)((addr & 0x3FFFF) >> 4) | ((uint64_t)(lbo >> 4) << 16) | ((uint64_t)(sbo >> 4) << 32) | (1ull << 62);
}
DEVINL void mma16816(float (&c)[4], uint32_t a0, uint32_t a1, uint32_t a2, uint32_t a3, uint32_t b0, uint32_t b1) {
  asm volatile(
      "mma.sync.aligned.m16n8k16.row.col.f32.bf16.bf16.f32 {%0,%1,%2,%3}, {%4,%5,%6,%7}, {%8,%9}, {%0,%1,%2,%3};"
      : "+f"(c[0]), "+f"(c[1]), "+f"(c[2]), "+f"(c[3])
      : "r"(a0), "r"(a1), "r"(a2), "r"(a3), "r"(b0), "r"(b1));
}
DEVINL void ldsm_x4(uint32_t& r0, uint32_t& r1, uint32_t& r2, uint32_t& r3, uint32_t addr) {
  asm volatile("ldmatrix.sync.aligned.m8n8.x4.shared.b16 {%0,%1,%2,%3}, [%4];"
               : "=r"(r0), "=r"(r1), "=r"(r2), "=r"(r3) : "r"(addr) : "memory");
}
DEVINL void ldsm_x4_t(uint32_t& r0, uint32_t& r1, uint32_t& r2, uint32_t& r3, uint32_t addr) {
  asm volatile("ldmatrix.sync.aligned.m8n8.x4.trans.shared.b16 {%0,%1,%2,%3}, [%4];"
               : "=r"(r0), "=r"(r1), "=r"(r2), "=r"(r3) : "r"(addr) : "memory");
}
DEVINL void stsm_x4(uint32_t addr, uint32_t r0, uint32_t r1, uint32_t r2, uint32_t r3) {
  asm volatile("stmatrix.sync.aligned.m8n8.x4.shared.b16 [%0], {%1,%2,%3,%4};" ::"r"(addr), "r"(r0), "r"(r1), "r"(r2), "r"(r3) : "memory");
}
DEVINL void stsm_x4_t(uint32_t addr, uint32_t r0, uint32_t r1, uint32_t r2, uint32_t r3) {
  asm volatile("stmatrix.sync.aligned.m8n8.x4.trans.shared.b16 [%0], {%1,%2,%3,%4};" ::"r"(addr), "r"(r0), "r"(r1), "r"(r2), "r"(r3) : "memory");
}
DEVINL uint32_t lds32(uint32_t a) { uint32_t v; asm volatile("ld.shared.b32 %0, [%1];" : "=r"(v) : "r"(a) : "memory"); return v; }
DEVINL uint4 lds128(uint32_t a) {
  uint4 v;
  asm volatile("ld.shared.v4.b32 {%0,%1,%2,%3}, [%4];" : "=r"(v.x), "=r"(v.y), "=r"(v.z), "=r"(v.w) : "r"(a) : "memory");
  return v;
}
DEVINL void sts32(uint32_t a, uint32_t v) { asm volatile("st.shared.b32 [%0], %1;" ::"r"(a), "r"(v) : "memory"); }
DEVINL void sts16(uint32_t a, uint16_t v) { asm volatile("st.shared.b16 [%0], %1;" ::"r"(a), "h"(v) : "memory"); }
DEVINL void sts128(uint32_t a, uint32_t x, uint32_t y, uint32_t z, uint32_t w) {
  asm volatile("st.shared.v4.b32 [%0], {%1,%2,%3,%4};" ::"r"(a), "r"(x), "r"(y), "r"(z), "r"(w) : "memory");
}
DEVINL uint4 ld_relaxed_v4(const void* p) {
  uint4 v;
  asm volatile("ld.relaxed.gpu.global.v4.b32 {%0,%1,%2,%3}, [%4];" : "=r"(v.x), "=r"(v.y), "=r"(v.z), "=r"(v.w) : "l"(p) : "memory");
  return v;
}
DEVINL uint32_t ld_relaxed(const void* p) {
  uint32_t v;
  asm volatile("ld.relaxed.gpu.global.b32 %0, [%1];" : "=r"(v) : "l"(p) : "memory");
  return v;
}
DEVINL uint32_t ld_acquire(const void* p) {
  uint32_t v;
  asm volatile("ld.acquire.gpu.global.b32 %0, [%1];" : "=r"(v) : "l"(p) : "memory");
  return v;
}
DEVINL void st_relaxed_v4(void* p, uint32_t x, uint32_t y, uint32_t z, uint32_t w) {
  asm volatile("st.relaxed.gpu.global.v4.b32 [%0], {%1,%2,%3,%4};" ::"l"(p), "r"(x), "r"(y), "r"(z), "r"(w) : "memory");
}
DEVINL uint32_t pack2(float lo, float hi) {
  uint32_t r;
  asm("cvt.rn.bf16x2.f32 %0, %1, %2;" : "=r"(r) : "f"(hi), "f"(lo));
  return r;
}
DEVINL float bf_lo(uint32_t w) { return __uint_as_float(w << 16); }
DEVINL float bf_hi(uint32_t w) { return __uint_as_float(w & 0xFFFF0000u); }
DEVINL float bf_round(float v) { return __bfloat162float(__float2bfloat16_rn(v)); }
DEVINL uint32_t hmax2(uint32_t a, uint32_t b) { uint32_t r; asm("max.bf16x2 %0, %1, %2;" : "=r"(r) : "r"(a), "r"(b)); return r; }
DEVINL uint32_t hmin2(uint32_t a, uint32_t b) { uint32_t r; asm("min.bf16x2 %0, %1, %2;" : "=r"(r) : "r"(a), "r"(b)); return r; }
DEVINL float ex2f(float x) { float r; asm("ex2.approx.ftz.f32 %0, %1;" : "=f"(r) : "f"(x)); return r; }
DEVINL float rcpf(float x) { float r; asm("rcp.approx.ftz.f32 %0, %1;" : "=f"(r) : "f"(x)); return r; }

__device__ __forceinline__ void wgmma_ss_n192(float (&d)[96], uint64_t da, uint64_t db, int scale_d) {
  asm volatile("{\n.reg .pred p;\nsetp.ne.b32 p, %98, 0;\n"
    "wgmma.mma_async.sync.aligned.m64n192k16.f32.bf16.bf16 "
    "{%0, %1, %2, %3, %4, %5, %6, %7, %8, %9, %10, %11, %12, %13, %14, %15, %16, %17, %18, %19, %20, %21, %22, %23, %24, %25, %26, %27, %28, %29, %30, %31, %32, %33, %34, %35, %36, %37, %38, %39, %40, %41, %42, %43, %44, %45, %46, %47, %48, %49, %50, %51, %52, %53, %54, %55, %56, %57, %58, %59, %60, %61, %62, %63, %64, %65, %66, %67, %68, %69, %70, %71, %72, %73, %74, %75, %76, %77, %78, %79, %80, %81, %82, %83, %84, %85, %86, %87, %88, %89, %90, %91, %92, %93, %94, %95}, %96, %97, p, 1, 1, 0, 1;\n}\n"
    : "+f"(d[0]), "+f"(d[1]), "+f"(d[2]), "+f"(d[3]), "+f"(d[4]), "+f"(d[5]), "+f"(d[6]), "+f"(d[7]), "+f"(d[8]), "+f"(d[9]), "+f"(d[10]), "+f"(d[11]), "+f"(d[12]), "+f"(d[13]), "+f"(d[14]), "+f"(d[15]), "+f"(d[16]), "+f"(d[17]), "+f"(d[18]), "+f"(d[19]), "+f"(d[20]), "+f"(d[21]), "+f"(d[22]), "+f"(d[23]), "+f"(d[24]), "+f"(d[25]), "+f"(d[26]), "+f"(d[27]), "+f"(d[28]), "+f"(d[29]), "+f"(d[30]), "+f"(d[31]), "+f"(d[32]), "+f"(d[33]), "+f"(d[34]), "+f"(d[35]), "+f"(d[36]), "+f"(d[37]), "+f"(d[38]), "+f"(d[39]), "+f"(d[40]), "+f"(d[41]), "+f"(d[42]), "+f"(d[43]), "+f"(d[44]), "+f"(d[45]), "+f"(d[46]), "+f"(d[47]), "+f"(d[48]), "+f"(d[49]), "+f"(d[50]), "+f"(d[51]), "+f"(d[52]), "+f"(d[53]), "+f"(d[54]), "+f"(d[55]), "+f"(d[56]), "+f"(d[57]), "+f"(d[58]), "+f"(d[59]), "+f"(d[60]), "+f"(d[61]), "+f"(d[62]), "+f"(d[63]), "+f"(d[64]), "+f"(d[65]), "+f"(d[66]), "+f"(d[67]), "+f"(d[68]), "+f"(d[69]), "+f"(d[70]), "+f"(d[71]), "+f"(d[72]), "+f"(d[73]), "+f"(d[74]), "+f"(d[75]), "+f"(d[76]), "+f"(d[77]), "+f"(d[78]), "+f"(d[79]), "+f"(d[80]), "+f"(d[81]), "+f"(d[82]), "+f"(d[83]), "+f"(d[84]), "+f"(d[85]), "+f"(d[86]), "+f"(d[87]), "+f"(d[88]), "+f"(d[89]), "+f"(d[90]), "+f"(d[91]), "+f"(d[92]), "+f"(d[93]), "+f"(d[94]), "+f"(d[95])
    : "l"(da), "l"(db), "r"(scale_d));
}

__device__ __forceinline__ void wgmma_ss_n128(float (&d)[64], uint64_t da, uint64_t db, int scale_d) {
  asm volatile("{\n.reg .pred p;\nsetp.ne.b32 p, %66, 0;\n"
    "wgmma.mma_async.sync.aligned.m64n128k16.f32.bf16.bf16 "
    "{%0, %1, %2, %3, %4, %5, %6, %7, %8, %9, %10, %11, %12, %13, %14, %15, %16, %17, %18, %19, %20, %21, %22, %23, %24, %25, %26, %27, %28, %29, %30, %31, %32, %33, %34, %35, %36, %37, %38, %39, %40, %41, %42, %43, %44, %45, %46, %47, %48, %49, %50, %51, %52, %53, %54, %55, %56, %57, %58, %59, %60, %61, %62, %63}, %64, %65, p, 1, 1, 0, 1;\n}\n"
    : "+f"(d[0]), "+f"(d[1]), "+f"(d[2]), "+f"(d[3]), "+f"(d[4]), "+f"(d[5]), "+f"(d[6]), "+f"(d[7]), "+f"(d[8]), "+f"(d[9]), "+f"(d[10]), "+f"(d[11]), "+f"(d[12]), "+f"(d[13]), "+f"(d[14]), "+f"(d[15]), "+f"(d[16]), "+f"(d[17]), "+f"(d[18]), "+f"(d[19]), "+f"(d[20]), "+f"(d[21]), "+f"(d[22]), "+f"(d[23]), "+f"(d[24]), "+f"(d[25]), "+f"(d[26]), "+f"(d[27]), "+f"(d[28]), "+f"(d[29]), "+f"(d[30]), "+f"(d[31]), "+f"(d[32]), "+f"(d[33]), "+f"(d[34]), "+f"(d[35]), "+f"(d[36]), "+f"(d[37]), "+f"(d[38]), "+f"(d[39]), "+f"(d[40]), "+f"(d[41]), "+f"(d[42]), "+f"(d[43]), "+f"(d[44]), "+f"(d[45]), "+f"(d[46]), "+f"(d[47]), "+f"(d[48]), "+f"(d[49]), "+f"(d[50]), "+f"(d[51]), "+f"(d[52]), "+f"(d[53]), "+f"(d[54]), "+f"(d[55]), "+f"(d[56]), "+f"(d[57]), "+f"(d[58]), "+f"(d[59]), "+f"(d[60]), "+f"(d[61]), "+f"(d[62]), "+f"(d[63])
    : "l"(da), "l"(db), "r"(scale_d));
}


constexpr float LOG2E = 1.4426950408889634f;

DEVINL uint32_t hadd2(uint32_t a, uint32_t b) { uint32_t r; asm("add.rn.bf16x2 %0, %1, %2;" : "=r"(r) : "r"(a), "r"(b)); return r; }
DEVINL uint32_t xw(uint32_t a, uint32_t b) { return __byte_perm(a, b, 0x5432); }
DEVINL void red_add(unsigned* p, unsigned v) { asm volatile("red.relaxed.gpu.global.add.u32 [%0], %1;" ::"l"(p), "r"(v) : "memory"); }
DEVINL void wait_cnt(const unsigned* p, unsigned target) {
  int it = 0;
#pragma unroll 1
  while ((int)(ld_relaxed(p) - target) < 0) {
    __nanosleep(64);
    if (++it > SPIN_LIMIT) break;
  }
  (void)ld_acquire(p);
}
DEVINL void sts64(uint32_t a, uint32_t x, uint32_t y) { asm volatile("st.shared.v2.b32 [%0], {%1,%2};" ::"r"(a), "r"(x), "r"(y) : "memory"); }
DEVINL uint2 lds64(uint32_t a) {
  uint2 v;
  asm volatile("ld.shared.v2.b32 {%0,%1}, [%2];" : "=r"(v.x), "=r"(v.y) : "r"(a) : "memory");
  return v;
}
DEVINL void mma16808(float (&c)[4], uint32_t a0, uint32_t a1, uint32_t b0) {
  asm volatile("mma.sync.aligned.m16n8k8.row.col.f32.bf16.bf16.f32 {%0,%1,%2,%3}, {%4,%5}, {%6}, {%0,%1,%2,%3};"
      : "+f"(c[0]), "+f"(c[1]), "+f"(c[2]), "+f"(c[3]) : "r"(a0), "r"(a1), "r"(b0));
}
DEVINL void ldsm_r(uint32_t* r, uint32_t addr) { ldsm_x4(r[0], r[1], r[2], r[3], addr); }
DEVINL void ldsm_tr(uint32_t* r, uint32_t addr) { ldsm_x4_t(r[0], r[1], r[2], r[3], addr); }
DEVINL void lds128_r(uint32_t* r, uint32_t a) { const uint4 v = lds128(a); r[0] = v.x; r[1] = v.y; r[2] = v.z; r[3] = v.w; }
DEVINL void tma_store_2d(const CUtensorMap* tm, uint32_t src, int c0, int c1) {
  asm volatile("cp.async.bulk.tensor.2d.global.shared::cta.bulk_group [%0, {%2, %3}], [%1];"
               ::"l"(tm), "r"(src), "r"(c0), "r"(c1) : "memory");
  asm volatile("cp.async.bulk.commit_group;" ::: "memory");
}

DEVINL void fence_async_global() { asm volatile("fence.proxy.async.global;" ::: "memory"); }

DEVINL int uch(int c) { return (c * 16) ^ ((c & 8) << 1); }
DEVINL void lda(uint32_t* r, uint32_t a) {
  asm volatile("ld.volatile.shared.b32 %0, [%4];\nld.volatile.shared.b32 %1, [%4+32];\nld.volatile.shared.b32 %2, [%4+-32];\nld.volatile.shared.b32 %3, [%4];"
               : "=r"(r[0]), "=r"(r[1]), "=r"(r[2]), "=r"(r[3]) : "r"(a) : "memory");
}
DEVINL void sts128_if(bool on, uint32_t a, uint32_t x, uint32_t y, uint32_t z, uint32_t w) {
  asm volatile("{\n.reg .pred q;\nsetp.ne.u32 q, %5, 0;\n@q st.shared.v4.b32 [%0], {%1,%2,%3,%4};\n}" ::"r"(a), "r"(x), "r"(y), "r"(z), "r"(w), "r"((uint32_t)on) : "memory");
}
DEVINL void red_v4(float4* p, float a, float b, float c) {
  asm volatile("red.relaxed.gpu.global.add.v4.f32 [%0], {%1, %2, %3, %4};" ::"l"(p), "f"(a), "f"(b), "f"(c), "f"(1.f) : "memory");
}
DEVINL unsigned short ldg16_now(const void* p) {
  unsigned short v;
  asm volatile("ld.global.nc.u16 %0, [%1];" : "=h"(v) : "l"(p));
  return v;
}
DEVINL uint32_t hmul2(uint32_t a, uint32_t b) { uint32_t r; asm("mul.rn.bf16x2 %0, %1, %2;" : "=r"(r) : "r"(a), "r"(b)); return r; }
DEVINL uint32_t hfma2(uint32_t a, uint32_t b, uint32_t c) { uint32_t r; asm("fma.rn.bf16x2 %0, %1, %2, %3;" : "=r"(r) : "r"(a), "r"(b), "r"(c)); return r; }
struct cplx { float re, im; };
DEVINL cplx cmul(cplx a, cplx b) { return {a.re * b.re - a.im * b.im, a.re * b.im + a.im * b.re}; }
DEVINL cplx csqr(cplx a) { return {a.re * a.re - a.im * a.im, (a.re + a.re) * a.im}; }
DEVINL cplx cexp_p(float ar2, float ang, float p) {
  const float m = ex2f(ar2 * p), th = ang * p;
  return {m * __cosf(th), m * __sinf(th)};
}

template <int LQ, int E, int K0, int K1>
DEVINL void conv_seg(float (&acc)[16][4], uint32_t (&R)[64], uint32_t arow) {
  constexpr int KST = 32 << LQ;
  ldsm_tr(&R[24], arow);
  ldsm_tr(&R[28], arow + KST);
#pragma unroll
  for (int k = K0; k <= K1; k++) {
    const int cur = 24 + 4 * ((k - K0) % 3), nxt = 24 + 4 * ((k - K0 + 2) % 3);
    if (k + 2 <= K1) ldsm_tr(&R[nxt], arow + (k + 2 - K0) * KST);
#pragma unroll
    for (int T = 0; T < 16; T++) {
      const int e = k - (8 >> LQ) * T + 16;
      if (e >= 0 && e < E) mma16816(acc[T], R[cur], R[cur + 1], R[cur + 2], R[cur + 3], R[2 * e], R[2 * e + 1]);
    }
  }
}
template <int E>
DEVINL void load_taps(uint32_t (&R)[64], uint32_t ta) {
#pragma unroll
  for (int e = 0; e < E; e++) { R[2 * e] = lds32(ta - e * 32); R[2 * e + 1] = lds32(ta - e * 32 - 16); }
}

__global__ void __launch_bounds__(512, 1)
fused_kernel(const __grid_constant__ CUtensorMap tm_x, const __grid_constant__ CUtensorMap tm_w,
             const __grid_constant__ CUtensorMap tm_wo,
             const __grid_constant__ CUtensorMap tm_out, const __grid_constant__ CUtensorMap tm_os,
             const __grid_constant__ CUtensorMap tm_ol, const __grid_constant__ CUtensorMap tm_xs,
             const __grid_constant__ CUtensorMap tm_xl, const __nv_bfloat16* __restrict__ x,
             const __nv_bfloat16* __restrict__ wphi,
             const __nv_bfloat16* __restrict__ logAr, const __nv_bfloat16* __restrict__ Aim,
             const __nv_bfloat16* __restrict__ Cre, const __nv_bfloat16* __restrict__ Cim,
             const __nv_bfloat16* __restrict__ logdt, const __nv_bfloat16* __restrict__ Dskip,
             const __nv_bfloat16* __restrict__ gatew) {
  extern __shared__ __align__(1024) unsigned char smem[];
  const uint32_t sb = smem_u32(smem);
  const int tid = threadIdx.x, warp = __shfl_sync(0xffffffffu, tid >> 5, 0), lane = tid & 31;
  const int wgi = __shfl_sync(0xffffffffu, tid >> 7, 0);
  const int g = lane >> 2, t = lane & 3;
  const int mi = lane >> 3, l7 = lane & 7;
  const int bid = blockIdx.x;
  const int hg_in = bid & 3, rt = (bid >> 2) & 15, hgblk = bid >> 6;
  const int hg = hgblk * 4 + hg_in;

  const uint32_t bar_full = sb + OFF_BAR;
  const uint32_t bar_empty = sb + OFF_BAR + 32;
  const uint32_t bar_full2 = sb + OFF_BAR + 64;
  const uint32_t bar_empty2 = sb + OFF_BAR + 128;
  const uint32_t bar_y = sb + OFF_BAR + 152;
  const uint32_t bar_vfree = sb + OFF_BAR + 160;
  const uint32_t bar_qfree = sb + OFF_BAR + 168;
  const uint32_t bar_aux = sb + OFF_BAR + 176;
  const uint32_t bar_ssm = sb + OFF_BAR + 184;
  const uint32_t bar_kv = sb + OFF_BAR + 192;
  const uint32_t bar_u = sb + OFF_BAR + 200;
  const uint32_t bar_mdone = sb + OFF_BAR + 208;
  const uint32_t bar_s0 = sb + OFF_BAR + 216;
  const uint32_t bar_xfree = sb + OFF_BAR + 224;
  const uint32_t bar_gw = sb + OFF_BAR + 232;
  const uint32_t bar_kg = sb + OFF_BAR + 240;
  const uint32_t bar_near = sb + OFF_BAR + 256;
  const uint32_t sm_epoch = sb + OFF_BAR + 384;


  if (wgi == 3) asm volatile("setmaxnreg.dec.sync.aligned.u32 56;");
  const int kch = hg * 64 + rt * 4 + (warp & 3);
  unsigned short q[16], rdt = 0;
  if (wgi == 2) {
    rdt = ldg16_now(logdt + kch);
#pragma unroll
    for (int i = 0; i < 4; i++) {
      const int n = kch * 128 + 32 * i + lane;
      q[4 * i] = ldg16_now(logAr + n); q[4 * i + 1] = ldg16_now(Aim + n);
      q[4 * i + 2] = ldg16_now(Cre + n); q[4 * i + 3] = ldg16_now(Cim + n);
    }
  }
  if (tid == 128) {
#pragma unroll
    for (int i = 0; i < 4; i++) mbar_init(bar_full + 8 * i, 1);
    asm volatile("fence.mbarrier_init.release.cluster;" ::: "memory");
#pragma unroll 1
    for (int st = 0; st < 4; st++) {
      const int k0 = (4 * hgblk + ((st + hg_in + 1) & 3)) * 64;
      const uint32_t dst = sb + OFF_RING + st * STAGE_BYTES;
      mbar_expect_tx(bar_full + 8 * st, STAGE_BYTES);
      tma_load_2d(dst, &tm_x, k0, rt * 128, bar_full + 8 * st);
      tma_load_2d(dst + 2 * BLK, &tm_w, hg * 64, k0, bar_full + 8 * st);
      tma_load_2d(dst + 3 * BLK, &tm_w, 512 + hg * 64, k0, bar_full + 8 * st);
      tma_load_2d(dst + 4 * BLK, &tm_w, 1024 + hg * 64, k0, bar_full + 8 * st);
    }
  }
  if (tid == 160) {
    constexpr unsigned long long c0 = 0x1111111188881111ull, c1 = 0x4422881341884414ull;
#pragma unroll
    for (int i = 4; i < 32; i++) mbar_init(sb + OFF_BAR + 8 * i, (int)(((i < 16 ? c0 : c1) >> (4 * (i & 15))) & 15));
    mbar_init(bar_near, 12);
    asm volatile("fence.mbarrier_init.release.cluster;" ::: "memory");
  }
  __syncwarp();
  if (wgi == 2) {
    asm volatile("bar.arrive 0, 512;" ::: "memory");
    asm volatile("setmaxnreg.inc.sync.aligned.u32 152;");
    const int w = warp - 8;
    const int ch = kch;
    const uint32_t park = sb + OFF_SSM + w * PARK;
    const uint32_t park2 = sb + 3 * BLK + w * PARK;
    const uint32_t tab = sb + OFF_TAB + w * 2048;
    const uint32_t ub = sb + OFF_U + w * UST + 512;
    const float dsk = bf_lo(__ldg((const unsigned short*)Dskip + ch));
    uint32_t W[56], R[64];
    float klast = 0.f, ka[5][4];
  auto kstore = [&](const uint32_t* V, uint32_t xb) {
    const uint32_t qa = xb + g * 512 + t * 16, ra = xb + 4096 + g * 256 + t * 8, sa = xb + 6144 + g * 128 + t * 4;
#pragma unroll
    for (int gg = 0; gg < 8; gg++) {
      sts128(qa + ((gg ^ (g & 1)) << 6), V[7 * gg], V[7 * gg + 1], V[7 * gg + 2], V[7 * gg + 3]);
      sts64(ra + ((gg ^ (g & 3)) << 5), V[7 * gg + 4], V[7 * gg + 5]);
      sts32(sa + ((gg ^ g) << 4), V[7 * gg + 6]);
    }
  };
    {
      uint32_t pa[4] = {0, 0, 0, 0}, pc[4] = {0, 0, 0, 0};
      float dt = 1.f;
#pragma unroll 1
      for (int u = 0; u < 4; u++) {
        if (u == 0) {
#pragma unroll
          for (int i = 0; i < 4; i++) { pa[i] = q[4 * i] | ((uint32_t)q[4 * i + 1] << 16); pc[i] = q[4 * i + 2] | ((uint32_t)q[4 * i + 3] << 16); }
          dt = bf_round(expf(bf_lo(rdt)));
        }
        if (u == 3) {
#pragma unroll
          for (int i = 0; i < 56; i++) R[i] = W[i];
        }
        const float fa = bf_lo(pa[0]), fi = bf_hi(pa[0]), fr = bf_lo(pc[0]), fc = bf_hi(pc[0]);
        pa[0] = pa[1]; pa[1] = pa[2]; pa[2] = pa[3]; pc[0] = pc[1]; pc[1] = pc[2]; pc[2] = pc[3];
        const float ar2 = -bf_round(expf(fa)) * dt * LOG2E;
        const float ang = fi * dt;
        const cplx C = {2.f * fr * dt, 2.f * fc * dt};
        const cplx w1 = cexp_p(ar2, ang, 1.f), W128 = cexp_p(ar2, ang, 128.f), m2b = cexp_p(ar2, ang, 244.f);
        const cplx E2 = csqr(w1), m2a = csqr(E2), m3a = csqr(m2a), E16 = csqr(m3a), m3b = cmul(m2b, m2a);
        const cplx W256 = csqr(W128), W512 = csqr(W256), W1024 = csqr(W512), W2048 = csqr(W1024);
        klast += C.re * W2048.re - C.im * W2048.im;
        cplx Al = {1.f, 0.f}, Be = C, S2 = cmul(C, W512), S3 = cmul(C, W1024);
        const uint32_t hc = pack2(W128.re, W128.re), hs = pack2(W128.im, -W128.im);
        const uint32_t oc = pack2(w1.re, w1.re), os2 = pack2(-w1.im, w1.im), bc = pack2(W256.re, W256.re), bs = pack2(-W256.im, W256.im);
#pragma unroll
        for (int gg = 0; gg < 8; gg++) {
          const uint32_t al = pack2(Al.re, -Al.im), be = pack2(Be.re, Be.im), bw = __byte_perm(be, 0, 0x1032);
          W[7 * gg] = al; W[7 * gg + 1] = hfma2(__byte_perm(al, 0, 0x1032), hs, hmul2(al, hc)); W[7 * gg + 2] = be;
          W[7 * gg + 3] = hfma2(bw, os2, hmul2(be, oc)); W[7 * gg + 4] = hfma2(bw, bs, hmul2(be, bc)); W[7 * gg + 5] = pack2(S2.re, S2.im);
          W[7 * gg + 6] = pack2(S3.re, S3.im);
          if (gg < 7) {
            Al = gg ? cmul(Al, E16) : E16;
            Be = cmul(Be, E2);
            S2 = cmul(S2, gg == 3 ? m2b : m2a);
            S3 = cmul(S3, (gg & 1) ? m3b : m3a);
          }
        }
        if (u < 2) kstore(W, park + (u & 1) * 7168);
      }
    }
    asm volatile("bar.sync 3, 160;" ::: "memory");
    mbar_wait(bar_mdone, 0);
    kstore(W, park2);
    kstore(R, park2 + 7168);
#pragma unroll
    for (int s = 0; s < 5; s++) { ka[s][0] = ka[s][1] = ka[s][2] = ka[s][3] = 0.f; }
    __syncwarp();
#pragma unroll 1
    for (int u = 0; u < 4; u++) {
      const uint32_t xb = (u < 2 ? park : park2) + (u & 1) * 7168;
#pragma unroll
      for (int km = 0; km < 8; km++) {
        lds128_r(&R[8 * km], xb + km * 512 + ((lane ^ ((km & 1) << 2)) << 4));
        const uint2 r2 = lds64(xb + 4096 + km * 256 + ((lane ^ ((km & 3) << 2)) << 3));
        R[8 * km + 4] = r2.x; R[8 * km + 5] = r2.y;
        R[8 * km + 6] = lds32(xb + 6144 + km * 128 + ((lane ^ (km << 2)) << 2));
      }
#pragma unroll
      for (int km = 0; km < 8; km++)
#pragma unroll
        for (int s = 0; s < 5; s++) mma16808(ka[s], R[8 * km], R[8 * km + 1], R[8 * km + 2 + s]);
    }
    __syncwarp();
    if (lane == 0) mbar_arrive(bar_kg);
#pragma unroll
    for (int o = 16; o > 0; o >>= 1) klast += __shfl_xor_sync(0xffffffffu, klast, o);
    mbar_wait(bar_gw, 0);
    {
        const uint32_t kw = park + 12160;
        {
          const float k512 = __shfl_sync(0xffffffffu, ka[3][0], 0), k1024 = __shfl_sync(0xffffffffu, ka[4][0], 0);
          if (lane == 0) ka[0][0] += dsk;
          if (lane == 31) ka[2][3] -= k512;
          float plo = __shfl_up_sync(0xffffffffu, ka[1][1], 1), phi = __shfl_up_sync(0xffffffffu, ka[1][3], 1);
          float nlo = __shfl_down_sync(0xffffffffu, ka[2][0], 1), nhi = __shfl_down_sync(0xffffffffu, ka[2][2], 1);
          const float l31 = __shfl_sync(0xffffffffu, ka[1][1], 31), h31 = __shfl_sync(0xffffffffu, ka[1][3], 31);
          const float e0 = __shfl_sync(0xffffffffu, ka[2][2], 0);
          if (lane == 0) { plo = 0.f; phi = l31; }
          if (lane == 31) { nlo = e0; nhi = 0.f; }
          sts128(kw + 64 + lane * 16, pack2(ka[0][0], plo), pack2(ka[1][0], ka[0][0]), pack2(ka[0][1], ka[1][0]), pack2(ka[1][1], ka[0][1]));
          sts128(kw + 576 + lane * 16, pack2(ka[0][2], phi), pack2(ka[1][2], ka[0][2]), pack2(ka[0][3], ka[1][2]), pack2(ka[1][3], ka[0][3]));
          sts128(kw + 1088 + lane * 16, pack2(ka[2][0], lane ? ka[2][0] : h31), pack2(ka[2][0], ka[2][0]), pack2(ka[2][1], ka[2][0]), pack2(nlo, ka[2][1]));
          sts128(kw + 1600 + lane * 16, pack2(ka[2][2], ka[2][2]), pack2(ka[2][2], ka[2][2]), pack2(ka[2][3], ka[2][2]), pack2(nhi, ka[2][3]));
          sts32(kw + (lane < 16 ? lane * 4 : (512 + lane) * 4), 0u);
          const int dd = lane - 16;
          sts32(tab + lane * 4, pack2((dd == -4 || dd == -3) ? -k1024 : 0.f, (dd == -3 || dd == -2) ? -k1024 : 0.f));
          sts32(tab + 128 + lane * 4, pack2((dd == 12 || dd == 13) ? -k1024 : 0.f, (dd == 13 || dd == 14) ? -k1024 : 0.f));
          sts32(tab + 256 + lane * 4, pack2(dd >= 12 ? klast : 0.f, dd >= 13 ? klast : 0.f));
          const uint32_t tw = tab + 512;
#pragma unroll
          for (int s = 0; s < 2; s++) { sts32(tw + s * 512 + lane * 4, 0u); sts32(tw + s * 512 + 384 + lane * 4, 0u); }
          const int i2 = 32 + 2 * g + (t & 1) + 32 * (t >> 1);
          sts32(tw + i2 * 4, pack2(ka[3][1], ka[3][0]));
          sts32(tw + (i2 + 16) * 4, pack2(ka[3][3], ka[3][2]));
          const int i3 = 32 + g + 16 * t;
          sts32(tw + 512 + i3 * 4, pack2(ka[4][1], ka[4][0]));
          sts32(tw + 512 + (i3 + 8) * 4, pack2(ka[4][3], ka[4][2]));
        }
        mbar_wait(bar_u, 0);
        __syncwarp();
#pragma unroll 2
        for (int it = 0; it < 4; it++) {
          uint4 cu[2], nx[2], pv[2];
#pragma unroll
          for (int j = 0; j < 2; j++) {
            const int ci = it * 32 + lane + 96 * j - 16;
            cu[j] = lds128(ub + uch(ci)); nx[j] = lds128(ub + uch(ci + 1)); pv[j] = lds128(ub + uch(ci - 1));
          }
#pragma unroll
          for (int j = 0; j < 2; j++) {
            const int li = it * 32 + lane + 96 * j;
            const uint4 c = cu[j], n = nx[j], v = pv[j];
            const uint32_t xm = xw(v.w, c.x), x0 = xw(c.x, c.y), x1 = xw(c.y, c.z), x2 = xw(c.z, c.w), x3 = xw(c.w, n.x), x4 = xw(n.x, n.y), x5 = xw(n.y, n.z);
            const uint32_t s0 = hadd2(hadd2(xm, x0), c.x), s1 = hadd2(hadd2(x0, x1), c.y), s2 = hadd2(hadd2(x1, x2), c.z), s3 = hadd2(hadd2(x2, x3), c.w);
            const bool lo = j ? li < 211 : it < 3, hi = j ? li < 147 : it < 3;
            sts128_if(lo, park + li * 16, s2, s3, hadd2(hadd2(x3, x4), n.x), hadd2(hadd2(x4, x5), n.y));
            const uint32_t f0 = hadd2(hadd2(v.w, c.y), s0), f1 = hadd2(hadd2(c.x, c.z), s1), f2 = hadd2(hadd2(c.y, c.w), s2), f3 = hadd2(hadd2(c.z, n.x), s3);
            sts128_if(lo, park + 3504 + li * 16, f0, f1, f2, f3);
            const uint32_t h0 = hadd2(hadd2(xw(v.z, v.w), x1), f0), h1 = hadd2(hadd2(xm, x2), f1), h2 = hadd2(hadd2(x0, x3), f2), h3 = hadd2(hadd2(x1, x4), f3);
            sts128_if(hi, park + 6912 + li * 16, h0, h1, h2, h3);
            sts128_if(hi, park + 9344 + li * 16, hadd2(hadd2(v.z, c.z), h0), hadd2(hadd2(v.w, c.w), h1), hadd2(hadd2(c.x, n.x), h2),
                      hadd2(hadd2(c.y, n.y), h3));
          }
        }
        float acc[16][4];
#pragma unroll
        for (int T = 0; T < 16; T++) { acc[T][0] = acc[T][1] = acc[T][2] = acc[T][3] = 0.f; }
        const int c2 = l7 + 8 * (mi >> 1);
        const int r16 = (mi & 1) * 16;
        load_taps<10>(R, tab + 512 + (2 * g + 95 - t) * 4);
        __syncwarp();
        conv_seg<2, 10, -1, 23>(acc, R, park + ((c2 & 1) ? 3504 + ((c2 + 1) >> 1) * 16 : (c2 >> 1) * 16) + 128 + r16);
        load_taps<9>(R, tab + 1024 + (g + 95 - t) * 4);
        conv_seg<3, 9, -1, 7>(acc, R, park + ((c2 & 1) ? 9344 : 6912) + (1 + c2) * 16 + r16);
        __syncwarp();
        {
          const int uc = 2 * (l7 + (lane >> 4) * 8) + (mi & 1);
          const uint32_t kaddr = kw + (16 + g - 2 * t) * 4, caddr = tab + (16 + g - 2 * t) * 4;
          uint32_t* S = &R[32];
#pragma unroll
          for (int j = 0; j < 5; j++) ldsm_r(&R[4 * j], ub + uch(uc - 14) + j * 512);
          lda(&S[16], caddr + 128);
          lda(&S[20], caddr + 256);
          lda(&S[24], kaddr + 2048);
          lda(&S[28], caddr);
#pragma unroll
          for (int T = 7; T < 16; T++) mma16816(acc[T], S[16], S[17], S[18], S[19], R[2 * T - 14], R[2 * T - 13]);
          mma16816(acc[15], S[20], S[21], S[22], S[23], R[0], R[1]);
#pragma unroll
          for (int j = 0; j < 8; j++) ldsm_r(&R[4 * j], ub + uch(uc) + j * 512);
#pragma unroll
          for (int j = 0; j < 4; j++) lda(&S[4 * j], kaddr + j * 512);
#pragma unroll
          for (int T = 4; T < 16; T++) mma16816(acc[T], S[24], S[25], S[26], S[27], R[2 * T - 8], R[2 * T - 7]);
#pragma unroll
          for (int T = 8; T < 16; T++) mma16816(acc[T], S[28], S[29], S[30], S[31], R[2 * T - 16], R[2 * T - 15]);
          __syncwarp();
          if (lane == 0) mbar_arrive(bar_near);
#pragma unroll 1
          for (int mp = 0; mp < 4; mp++) {
#pragma unroll
            for (int hb = 0; hb < 2; hb++) {
              const int ml = 2 * mp + hb;
              uint32_t* Sc = &S[16 * hb];
              uint32_t* Sn = &S[16 - 16 * hb];
              const uint32_t kp = kaddr + ml * 64 + 64;
              const uint32_t uo = ub + uch(uc - 2 * ml), un = ub + uch(uc - 2 * ml - 2);
              {
#pragma unroll
                for (int j = 4; j < 8; j++) ldsm_r(&R[4 * j], uo + j * 512);
#pragma unroll
                for (int j = 0; j < 4; j++) lda(&Sn[4 * j], kp + j * 512);
#pragma unroll
                for (int m = 0; m < 4; m++)
#pragma unroll
                  for (int T = m; T < 8; T++) mma16816(acc[T], Sc[4 * m], Sc[4 * m + 1], Sc[4 * m + 2], Sc[4 * m + 3], R[2 * (T - m)], R[2 * (T - m) + 1]);
              }
              {
                ldsm_r(&R[0], un);
                ldsm_r(&R[4], un + 512);
#pragma unroll
                for (int m = 3; m >= 0; m--) {
#pragma unroll
                  for (int T = 8; T < 16; T++) mma16816(acc[T], Sc[4 * m], Sc[4 * m + 1], Sc[4 * m + 2], Sc[4 * m + 3], R[2 * (T - m)], R[2 * (T - m) + 1]);
                  if (m == 3) ldsm_r(&R[8], un + 2 * 512);
                  if (m == 1) ldsm_r(&R[12], un + 3 * 512);
                }
              }
            }
          }
        }
        __syncwarp();
        if (lane == 0) mbar_arrive(bar_ssm);
        {
          const uint32_t ya = park + 8192 + ((lane >> 4) * 128 + l7 * 16 + (mi & 1) * 8) * 2;
          const uint32_t tag = g == 0 ? 0x00010001u : 0u;
#pragma unroll
          for (int T = 0; T < 16; T += 2)
            stsm_x4_t(ya + T * 256, pack2(acc[T][0], acc[T][1]) | tag, pack2(acc[T][2], acc[T][3]) | tag,
                      pack2(acc[T + 1][0], acc[T + 1][1]) | tag, pack2(acc[T + 1][2], acc[T + 1][3]) | tag);
          mbar_wait(bar_empty2 + 8, 0);
          __syncwarp();
#pragma unroll
          for (int i = 0; i < 8; i++) lds128_r(&R[4 * i], park + 8192 + (i * 32 + lane) * 16);
#pragma unroll
          for (int i = 7; i >= 0; i--)
            st_relaxed_v4((uint4*)(g_yT + (size_t)ch * SEQ) + i * 32 + lane, R[4 * i], R[4 * i + 1], R[4 * i + 2], R[4 * i + 3]);
          uint4* src = (uint4*)(g_yT + (size_t)(hg_in * 128 + w * 32 + mi) * SEQ + rt * 128 + hgblk * 64) + l7;
          uint4 v[8];
#pragma unroll
          for (int i = 0; i < 8; i++) v[i].x = 0;
          __nanosleep(100);
#pragma unroll 1
          for (int it = 0; it < SPIN_LIMIT; it++) {
            uint32_t mn = 0xffffffffu;
#pragma unroll
            for (int i = 0; i < 8; i++)
              if (v[i].x == 0) v[i] = ld_relaxed_v4(src + i * (4 * SEQ / 8));
#pragma unroll
            for (int i = 0; i < 8; i++) mn = min(mn, v[i].x);
            if (mn != 0) break;
          }
          __syncwarp();
          mbar_wait(bar_empty2, 0);
#pragma unroll
          for (int i = 0; i < 8; i++) {
            const int c = w * 32 + i * 4 + mi;
            sts128(sb + 14 * BLK + c * 128 + ((l7 ^ (c & 7)) << 4), v[i].x, v[i].y, v[i].z, v[i].w);
          }
          __syncwarp();
          if (lane == 0) {
            mbar_arrive(bar_y);
          }
        }
    }
  } else if (wgi == 3) {
    if (warp == 12) {
      if (lane == 0) {
        asm volatile("prefetch.tensormap [%0];" ::"l"(&tm_xs) : "memory");
        asm volatile("prefetch.tensormap [%0];" ::"l"(&tm_xl) : "memory");
      }
      asm volatile("bar.sync 0, 512;" ::: "memory");
    }
    if (warp == 12) {
#pragma unroll 1
      for (int st = 0; st < 4; st++) {
        mbar_wait(bar_empty + 8 * st, 0);
        if (st == 3) mbar_wait(bar_xfree, 0);
        const int k0 = (4 + st - 4 * hgblk) * 64;
        const uint32_t dst = sb + OFF_RING + st * STAGE_BYTES;
        if (lane == 0) mbar_expect_tx(bar_full + 8 * st, STAGE_BYTES);
        __syncwarp();
        if (lane == 0) tma_load_2d(dst, &tm_x, k0, rt * 128, bar_full + 8 * st);
        else if (lane < 4) tma_load_2d(dst + (1 + lane) * BLK, &tm_w, (lane - 1) * 512 + hg * 64, k0, bar_full + 8 * st);
        __syncwarp();
      }
      mbar_wait(bar_aux, 0);
      {
        const unsigned target = (lds32(sm_epoch) & ~127u) + 128u;
        const uint32_t bar = bar_full2 + 8 * (lane & 7);
        const int cch = (lane + 4 * hgblk) & 7;
        const unsigned* flag = &g_ocnt[(rt * 2 + hgblk) * 8 + cch];
        if (lane < 8) mbar_expect_tx(bar, 3 * BLK);
        if (lane == 0) {
          asm volatile("prefetch.tensormap [%0];" ::"l"(&tm_os) : "memory");
          asm volatile("prefetch.tensormap [%0];" ::"l"(&tm_ol) : "memory");
        }
        mbar_wait(bar_near, 0);
        if (lane < 8) {
          tma_load_2d(sb + w_off(lane, 0), &tm_wo, hg_in * 128, cch * 64, bar);
          tma_load_2d(sb + w_off(lane, 1), &tm_wo, hg_in * 128 + 64, cch * 64, bar);
        }
        __syncwarp();
        mbar_wait(bar_qfree, 0);
        bool need = lane < 8;
#pragma unroll 1
        for (int it = 0; it < SPIN_LIMIT; it++) {
          if (need && (int)(ld_relaxed(flag) - target) >= 0) {
            (void)ld_acquire(flag);
            fence_async_global();
            if (lane < 6) tma_load_2d(sb + o_off(lane), &tm_ol, cch * 64, rt * 128 + hgblk * 64, bar);
            need = false;
          }
          if (!__any_sync(0xffffffffu, need)) break;
          __nanosleep(60);
        }
        if (lane == 0) asm volatile("prefetch.tensormap [%0];" ::"l"(&tm_out) : "memory");
        mbar_wait(bar_ssm, 0);
        if (lane == 6 || lane == 7) tma_load_2d(sb + o_off(lane), &tm_ol, cch * 64, rt * 128 + hgblk * 64, bar);
        if (lane == 0) red_add(&g_done, 1u);
      }
    } else {
      if (warp == 14) {
        const unsigned done = ld_relaxed(&g_done);
        asm volatile("bar.sync 0, 512;" ::: "memory");
        uint32_t w4[16];
#pragma unroll
        for (int i = 0; i < 16; i++) {
          const unsigned short* wb = (const unsigned short*)wphi + (hg * 4 + (i >> 2)) * 256 + 2 * t * 16 + g + (i & 1) * 128 + ((i >> 1) & 1) * 8;
          w4[i] = (uint32_t)__ldg(wb) | ((uint32_t)__ldg(wb + 16) << 16);
        }
#pragma unroll
        for (int h = 0; h < 4; h++) sts128(sb + OFF_WPHI + h * 512 + lane * 16, w4[4 * h], w4[4 * h + 1], w4[4 * h + 2], w4[4 * h + 3]);
        if (lane == 0) sts32(sm_epoch, done);
        __syncwarp();
        if (lane == 0) mbar_arrive(bar_aux);
        mbar_wait(bar_s0, 0);
#pragma unroll
        for (int i = 0; i < 4; i++) sts128(sb + OFF_U + i * UST + lane * 16, 0, 0, 0, 0);
        __syncwarp();
        if (lane == 0) {
          wait_cnt(&g_xcnt[hg * 32], (done & ~127u) + 128u);
          fence_async_global();
          mbar_expect_tx(bar_u, 16384);
#pragma unroll 1
          for (int i = 0; i < 4; i++) tma_load_2d(sb + OFF_U + i * UST + 512, &tm_xl, 0, (hg * 64 + rt * 4 + i) * 128, bar_u);
        }
        __syncwarp();
      } else {
        const int half = (warp - 13) >> 1;
        const int row0 = rt * 128 + hg * 16 + half * 8;
        const uint4* xr = (const uint4*)(x + (size_t)row0 * DM) + lane;
        float mine = 0.f;
        if (lane < 24) g_kva[hg * 768 + rt * 48 + half * 24 + lane] = make_float4(0.f, 0.f, 0.f, 0.f);
        asm volatile("bar.sync 0, 512;" ::: "memory");
        {
            mbar_wait(bar_full + 24, 0);
            const uint32_t stg = sb + OFF_TAB + half * 4096;
#pragma unroll 1
            for (int rd = 0; rd < 2; rd++) {
              const uint32_t src = sb + OFF_RING + 3 * STAGE_BYTES + (64 * half + 32 * rd + lane) * 128;
              uint32_t r[8][4];
#pragma unroll
              for (int cc = 0; cc < 8; cc++) ldsm_x4(r[cc][0], r[cc][1], r[cc][2], r[cc][3], src + ((cc ^ l7) << 4));
              if (rd == 1) {
                if (lane == 0) asm volatile("cp.async.bulk.wait_group.read 0;" ::: "memory");
                __syncwarp();
              }
#pragma unroll
              for (int cc = 0; cc < 8; cc++) stsm_x4_t(stg + (cc * 8 + l7) * 64 + ((mi ^ ((l7 >> 1) & 3)) << 4), r[cc][0], r[cc][1], r[cc][2], r[cc][3]);
              asm volatile("fence.proxy.async.shared::cta;" ::: "memory");
              __syncwarp();
              if (lane == 0) tma_store_2d(&tm_xs, stg, rt * 128 + 64 * half + 32 * rd, hg * 64);
            }
            if (lane == 0) mbar_arrive(bar_xfree);

            __threadfence();
            __syncwarp();
            if (lane == 0) {
              asm volatile("cp.async.bulk.wait_group 0;" ::: "memory");
              mbar_arrive(bar_gw);
              red_add(&g_xcnt[hg * 32], 4u);
            }
          }
#pragma unroll 1
        for (int b = 0; b < 2; b++) {
          const uint4 gw = __ldg((const uint4*)gatew + b * 32 + lane);
          uint4 a[8];
#pragma unroll
          for (int r = 0; r < 8; r++) a[r] = __ldg(xr + r * 64 + b * 32);
          float sr[8];
#pragma unroll
          for (int r = 0; r < 8; r++) {
            float s = bf_lo(a[r].x) * bf_lo(gw.x);
            s = fmaf(bf_hi(a[r].x), bf_hi(gw.x), s); s = fmaf(bf_lo(a[r].y), bf_lo(gw.y), s); s = fmaf(bf_hi(a[r].y), bf_hi(gw.y), s);
            s = fmaf(bf_lo(a[r].z), bf_lo(gw.z), s); s = fmaf(bf_hi(a[r].z), bf_hi(gw.z), s);
            s = fmaf(bf_lo(a[r].w), bf_lo(gw.w), s); sr[r] = fmaf(bf_hi(a[r].w), bf_hi(gw.w), s);
          }
#pragma unroll
          for (int i = 0; i < 4; i++) sr[i] = ((lane & 16) ? sr[i + 4] : sr[i]) + __shfl_xor_sync(0xffffffffu, (lane & 16) ? sr[i] : sr[i + 4], 16);
#pragma unroll
          for (int i = 0; i < 2; i++) sr[i] = ((lane & 8) ? sr[i + 2] : sr[i]) + __shfl_xor_sync(0xffffffffu, (lane & 8) ? sr[i] : sr[i + 2], 8);
          mine += ((lane & 4) ? sr[1] : sr[0]) + __shfl_xor_sync(0xffffffffu, (lane & 4) ? sr[0] : sr[1], 4);
        }
        mine += __shfl_xor_sync(0xffffffffu, mine, 1);
        mine += __shfl_xor_sync(0xffffffffu, mine, 2);
        if (t == 0) g_gate[row0 + g] = 1.f / (1.f + __expf(-mine));
        {
          uint4* yz = (uint4*)(g_yT + (size_t)(hg_in * 128 + half * 64 + mi) * SEQ + rt * 128 + hgblk * 64) + l7;
#pragma unroll 4
          for (int i = 0; i < 16; i++) yz[i * (4 * SEQ / 8)] = make_uint4(0, 0, 0, 0);
        }
        __threadfence();
        __syncwarp();
        if (lane == 0) red_add(&g_xcnt[(8 + half) * 32], 1u);
      }
      const int idx = (warp - 13) * 32 + lane;
      mbar_wait(bar_vfree, 0);
      {
        const float4* src = g_kva + hg * 768 + idx;
        const bool three = idx < 64;
        uint4 v[9];
#pragma unroll 1
        for (int it = 0; it < SPIN_LIMIT; it++) {
          bool ok = true;
#pragma unroll
          for (int i = 0; i < 9; i++)
            if (i < 6 || three) v[i] = ld_relaxed_v4(src + (i / 3) * 96 + (i % 3) * 256);
#pragma unroll
          for (int i = 0; i < 9; i++)
            if (i < 6 || three) ok = ok && v[i].w == 0x41800000u;
          if (ok) break;
          __nanosleep(100);
        }
        mbar_wait(bar_kg, 0);
#pragma unroll
        for (int r = 0; r < 3; r++) {
          if (r < 2 || three) {
            const int i = idx + 96 * r;
            const uint4 a = v[3 * r], b = v[3 * r + 1], c = v[3 * r + 2];
            sts128(sb + OFF_KV + i * 16, pack2(__uint_as_float(a.x), __uint_as_float(a.y)), pack2(__uint_as_float(a.z), __uint_as_float(b.x)),
                   pack2(__uint_as_float(b.y), __uint_as_float(b.z)), pack2(__uint_as_float(c.x), __uint_as_float(c.y)));
            if (g < 4) sts16(sb + OFF_KV + 4096 + (i >> 5) * 32 + t * 8 + g * 2, (uint16_t)pack2(__uint_as_float(c.z), 0.f));
          }
        }
        __syncwarp();
        if (lane == 0) mbar_arrive(bar_kv);
      }
      if (tid == 448) {
        const unsigned target = (lds32(sm_epoch) & ~127u) + 128u;
        wait_cnt(&g_xcnt[8 * 32], target);
        wait_cnt(&g_xcnt[9 * 32], target);
        mbar_arrive(bar_empty2 + 8);
      }
    }
  } else {
    if (warp == 5) asm volatile("bar.arrive 3, 160;" ::: "memory");
    asm volatile("bar.sync 0, 512;" ::: "memory");
    asm volatile("setmaxnreg.inc.sync.aligned.u32 152;");
    const int wg = wgi, wq = warp & 3;
    const int srow = warp * 16 + l7 + (mi & 1) * 8;
    const int hi16 = lane >> 4;
    const uint32_t ONE = 0x3F803F80u;
    uint32_t kq[8][4];
    {
      float d[96];
#pragma unroll 1
      for (int kc = 0; kc < 8; kc++) {
        const int st = kc & 3;
        mbar_wait(bar_full + 8 * st, kc >> 2);
        const uint32_t sa = sb + OFF_RING + st * STAGE_BYTES + wg * BLK;
        const uint32_t sw = sb + OFF_RING + st * STAGE_BYTES + 2 * BLK;
        wg_fence();
#pragma unroll
        for (int k = 0; k < 4; k++)
          wgmma_ss_n192(d, make_desc(sa + k * 32, 16, 1024), make_desc(sw + k * 2048, BLK, 1024), (kc | k) != 0);
        wg_commit();
        if (kc > 0) {
          wg_wait<1>();
          if (lane == 0) {
            mbar_arrive(bar_empty + 8 * ((kc - 1) & 3));
            if (kc == 5) mbar_arrive(bar_s0);
          }
        }
      }
      wg_wait<0>();
      if (lane == 0) mbar_arrive(bar_mdone);
#pragma unroll
      for (int h = 0; h < 4; h++)
#pragma unroll
        for (int i = 0; i < 4; i++) {
          kq[h][i] = pack2(d[32 + 8 * h + 2 * i], d[33 + 8 * h + 2 * i]);
          kq[4 + h][i] = pack2(d[8 * h + 2 * i], d[8 * h + 2 * i + 1]);
        }
      mbar_wait(bar_mdone, 0);
#pragma unroll
      for (int h = 0; h < 4; h++) {
        const int jv = 64 + 8 * h;
        stsm_x4(sb + OFF_VST + srow * 128 + (((2 * h + hi16) ^ l7) << 4), pack2(d[jv], d[jv + 1]), pack2(d[jv + 2], d[jv + 3]),
                pack2(d[jv + 4], d[jv + 5]), pack2(d[jv + 6], d[jv + 7]));
      }
    }
    mbar_wait(bar_aux, 0);
#pragma unroll 1
    for (int it = 0; it < 2; it++) {
      float ep[4][2][4], en[4][2][4];
      uint32_t lg[4][4];
      float pmin = 1.f;
      {
        uint4 wp[4];
        float c0[4][4], c1[4][4];
#pragma unroll
        for (int j = 0; j < 4; j++) wp[j] = lds128(sb + OFF_WPHI + j * 512 + lane * 16);
#pragma unroll
        for (int j = 0; j < 4; j++) {
#pragma unroll
          for (int i = 0; i < 4; i++) { c0[j][i] = 0.f; c1[j][i] = 0.f; }
          mma16816(c0[j], kq[j][0], kq[j][1], kq[j][2], kq[j][3], wp[j].x, wp[j].y);
          mma16816(c1[j], kq[j][0], kq[j][1], kq[j][2], kq[j][3], wp[j].z, wp[j].w);
        }
#pragma unroll
        for (int j = 0; j < 4; j++) {
          lg[j][0] = pack2(c0[j][0], c0[j][1]); lg[j][1] = pack2(c1[j][0], c1[j][1]);
          lg[j][2] = pack2(c0[j][2], c0[j][3]); lg[j][3] = pack2(c1[j][2], c1[j][3]);
        }
      }
#pragma unroll
      for (int j = 0; j < 4; j++) {
        const uint32_t ma = hmax2(lg[j][0], lg[j][1]), mb = hmax2(lg[j][2], lg[j][3]);
        uint32_t m = hmax2(__byte_perm(ma, mb, 0x5410), __byte_perm(ma, mb, 0x7632));
        m = hmax2(m, __shfl_xor_sync(0xffffffffu, m, 1));
        m = hmax2(m, __shfl_xor_sync(0xffffffffu, m, 2));
#pragma unroll
        for (int r = 0; r < 2; r++) {
          const float ml = -(r ? bf_hi(m) : bf_lo(m)) * LOG2E;
          float* e = ep[j][r];
          e[0] = ex2f(fmaf(bf_lo(lg[j][2 * r]), LOG2E, ml)); e[1] = ex2f(fmaf(bf_hi(lg[j][2 * r]), LOG2E, ml));
          e[2] = ex2f(fmaf(bf_lo(lg[j][2 * r + 1]), LOG2E, ml)); e[3] = ex2f(fmaf(bf_hi(lg[j][2 * r + 1]), LOG2E, ml));
          const float s01 = e[0] * e[1], s23 = e[2] * e[3], pr = s01 * s23, rr = rcpf(pr);
          const float i01 = rr * s23, i23 = rr * s01;
          en[j][r][0] = i01 * e[1]; en[j][r][1] = i01 * e[0]; en[j][r][2] = i23 * e[3]; en[j][r][3] = i23 * e[2];
          pmin = fminf(pmin, pr);
        }
      }
      if (__any_sync(0xffffffffu, !(pmin >= 7.9e-31f))) {
#pragma unroll
        for (int j = 0; j < 4; j++) {
          const uint32_t ma = hmin2(lg[j][0], lg[j][1]), mb = hmin2(lg[j][2], lg[j][3]);
          uint32_t m = hmin2(__byte_perm(ma, mb, 0x5410), __byte_perm(ma, mb, 0x7632));
          m = hmin2(m, __shfl_xor_sync(0xffffffffu, m, 1));
          m = hmin2(m, __shfl_xor_sync(0xffffffffu, m, 2));
#pragma unroll
          for (int r = 0; r < 2; r++) {
            const float ml = (r ? bf_hi(m) : bf_lo(m)) * LOG2E;
            en[j][r][0] = ex2f(fmaf(bf_lo(lg[j][2 * r]), -LOG2E, ml)); en[j][r][1] = ex2f(fmaf(bf_hi(lg[j][2 * r]), -LOG2E, ml));
            en[j][r][2] = ex2f(fmaf(bf_lo(lg[j][2 * r + 1]), -LOG2E, ml)); en[j][r][3] = ex2f(fmaf(bf_hi(lg[j][2 * r + 1]), -LOG2E, ml));
          }
        }
      }
      const uint32_t prow = sb + OFF_PHK + srow * 256;
      uint32_t Pk[4][4], Nk[4][4];
#pragma unroll
      for (int j = 0; j < 4; j++) {
        Pk[j][0] = pack2(ep[j][0][0], ep[j][0][1]); Pk[j][1] = pack2(ep[j][1][0], ep[j][1][1]);
        Pk[j][2] = pack2(ep[j][0][2], ep[j][0][3]); Pk[j][3] = pack2(ep[j][1][2], ep[j][1][3]);
        Nk[j][0] = pack2(en[j][0][0], en[j][0][1]); Nk[j][1] = pack2(en[j][1][0], en[j][1][1]);
        Nk[j][2] = pack2(en[j][0][2], en[j][0][3]); Nk[j][3] = pack2(en[j][1][2], en[j][1][3]);
      }
      if (it == 0) {
        float spa[4][4], sna[4][4];
#pragma unroll
        for (int j = 0; j < 4; j++) {
#pragma unroll
          for (int i = 0; i < 4; i++) { spa[j][i] = 0.f; sna[j][i] = 0.f; }
          mma16816(spa[j], Pk[j][0], Pk[j][1], Pk[j][2], Pk[j][3], ONE, ONE);
          mma16816(sna[j], Nk[j][0], Nk[j][1], Nk[j][2], Nk[j][3], ONE, ONE);
        }
#pragma unroll
        for (int j = 0; j < 4; j++) {
          const float r0 = rcpf(spa[j][0] * sna[j][0]), r1 = rcpf(spa[j][2] * sna[j][2]);
          const uint32_t c0 = pack2(r0 * sna[j][0], r0 * spa[j][0]), c1 = pack2(r1 * sna[j][2], r1 * spa[j][2]);
          const uint32_t p0 = __byte_perm(c0, 0, 0x1010), n0 = __byte_perm(c0, 0, 0x3232), p1 = __byte_perm(c1, 0, 0x1010), n1 = __byte_perm(c1, 0, 0x3232);
          Pk[j][0] = hmul2(Pk[j][0], p0); Pk[j][1] = hmul2(Pk[j][1], p1); Pk[j][2] = hmul2(Pk[j][2], p0); Pk[j][3] = hmul2(Pk[j][3], p1);
          Nk[j][0] = hmul2(Nk[j][0], n0); Nk[j][1] = hmul2(Nk[j][1], n1); Nk[j][2] = hmul2(Nk[j][2], n0); Nk[j][3] = hmul2(Nk[j][3], n1);
          stsm_x4(prow + (((4 * j + hi16) ^ l7) << 4), Pk[j][0], Pk[j][1], Pk[j][2], Pk[j][3]);
          stsm_x4(prow + (((4 * j + 2 + hi16) ^ l7) << 4), Nk[j][0], Nk[j][1], Nk[j][2], Nk[j][3]);
        }
#pragma unroll
        for (int i = 0; i < 16; i++) kq[i >> 2][i & 3] = kq[(i >> 2) + 4][i & 3];
      } else {
#pragma unroll
        for (int i = 0; i < 16; i++) { kq[i >> 2][i & 3] = Pk[i >> 2][i & 3]; kq[4 + (i >> 2)][i & 3] = Nk[i >> 2][i & 3]; }
      }
      if (it == 0) {
        named_bar(1, 256);
        const int hh = warp >> 1, ks = warp & 1;
        float D[2][4][4];
#pragma unroll
        for (int i = 0; i < 8; i++) { D[i >> 2][i & 3][0] = D[i >> 2][i & 3][1] = D[i >> 2][i & 3][2] = D[i >> 2][i & 3][3] = 0.f; }
        const uint32_t va = sb + OFF_VST + (l7 + (mi >> 1) * 8) * 128 + (((2 * hh + (mi & 1)) ^ l7) << 4);
        const uint32_t pa = sb + OFF_PHK + (l7 + (mi & 1) * 8) * 256 + (((4 * hh + 2 * ks + (mi >> 1)) ^ l7) << 4);
        uint32_t A[8][4], B[8][4];
#pragma unroll
        for (int s = 0; s < 8; s++) {
          ldsm_x4_t(A[s][0], A[s][1], A[s][2], A[s][3], va + s * 16 * 128);
          ldsm_x4_t(B[s][0], B[s][1], B[s][2], B[s][3], pa + s * 16 * 256);
        }
#pragma unroll
        for (int s = 0; s < 8; s++) {
          mma16816(D[s & 1][0], A[s][0], A[s][1], A[s][2], A[s][3], B[s][0], B[s][1]);
          mma16816(D[s & 1][1], A[s][0], A[s][1], A[s][2], A[s][3], B[s][2], B[s][3]);
          if (s & 1) {
            mma16816(D[(s >> 1) & 1][2], ONE, ONE, ONE, ONE, hadd2(B[s][0], B[s - 1][0]), hadd2(B[s][1], B[s - 1][1]));
            mma16816(D[(s >> 1) & 1][3], ONE, ONE, ONE, ONE, hadd2(B[s][2], B[s - 1][2]), hadd2(B[s][3], B[s - 1][3]));
          }
        }
        const float zz = (g & 2) ? ((g & 1) ? D[0][3][1] + D[1][3][1] : D[0][3][0] + D[1][3][0])
                                 : ((g & 1) ? D[0][2][1] + D[1][2][1] : D[0][2][0] + D[1][2][0]);
        float4* kp = g_kva + hg * 768 + tid;
        mbar_wait(bar_u, 0);
        red_v4(kp, D[0][0][0] + D[1][0][0], D[0][0][1] + D[1][0][1], D[0][1][0] + D[1][1][0]);
        red_v4(kp + 256, D[0][1][1] + D[1][1][1], D[0][0][2] + D[1][0][2], D[0][0][3] + D[1][0][3]);
        red_v4(kp + 512, D[0][1][2] + D[1][1][2], D[0][1][3] + D[1][1][3], zz);
        __syncwarp();
        if (lane == 0) { mbar_arrive(bar_vfree); mbar_arrive(bar_near); }
      }
    }
    const int row0 = rt * 128 + hgblk * 64 + wq * 16 + g;
    uint32_t gv0 = 0, gv1 = 0;
    const uint32_t os = sb + OFF_PHQ + warp * 2048;
    {
      uint32_t ow[4][4];
      mbar_wait(bar_kv, 0);
      uint4 kP[4], kN[4];
      uint2 zP[4], zN[4];
#pragma unroll
      for (int h = 0; h < 4; h++) {
        zP[h] = lds64(sb + OFF_KV + 4096 + h * 64 + t * 8); zN[h] = lds64(sb + OFF_KV + 4096 + h * 64 + 32 + t * 8);
        kP[h] = lds128(sb + OFF_KV + h * 1024 + lane * 16);
        kN[h] = lds128(sb + OFF_KV + h * 1024 + 512 + lane * 16);
      }
#pragma unroll
      for (int h = 0; h < 4; h++) {
        float P0[4] = {0.f, 0.f, 0.f, 0.f}, P1[4] = {0.f, 0.f, 0.f, 0.f}, PZ[4] = {0.f, 0.f, 0.f, 0.f};
        float N0[4] = {0.f, 0.f, 0.f, 0.f}, N1[4] = {0.f, 0.f, 0.f, 0.f}, NZ[4] = {0.f, 0.f, 0.f, 0.f};
        mma16816(PZ, kq[h][0], kq[h][1], kq[h][2], kq[h][3], (g & 1) ? ONE : zP[h].x, (g & 1) ? ONE : zP[h].y);
        mma16816(NZ, kq[4 + h][0], kq[4 + h][1], kq[4 + h][2], kq[4 + h][3], (g & 1) ? ONE : zN[h].x, (g & 1) ? ONE : zN[h].y);
        mma16816(P0, kq[h][0], kq[h][1], kq[h][2], kq[h][3], kP[h].x, kP[h].y);
        mma16816(P1, kq[h][0], kq[h][1], kq[h][2], kq[h][3], kP[h].z, kP[h].w);
        mma16816(N0, kq[4 + h][0], kq[4 + h][1], kq[4 + h][2], kq[4 + h][3], kN[h].x, kN[h].y);
        mma16816(N1, kq[4 + h][0], kq[4 + h][1], kq[4 + h][2], kq[4 + h][3], kN[h].z, kN[h].w);
#pragma unroll
        for (int r = 0; r < 2; r++) {
          const float rn = rcpf(NZ[2 * r + 1]), sp = PZ[2 * r + 1] * rn;
          const float id = rcpf(fmaf(NZ[2 * r], sp, fmaf(1e-6f, PZ[2 * r + 1], PZ[2 * r])));
          const float fN = sp * id;
          ow[h][r] = pack2(fmaf(P0[2 * r], id, N0[2 * r] * fN), fmaf(P0[2 * r + 1], id, N0[2 * r + 1] * fN));
          ow[h][2 + r] = pack2(fmaf(P1[2 * r], id, N1[2 * r] * fN), fmaf(P1[2 * r + 1], id, N1[2 * r + 1] * fN));
        }
      }
#pragma unroll
      for (int h = 0; h < 4; h++)
        stsm_x4(os + (l7 + (mi & 1) * 8) * 128 + (((2 * h + hi16) ^ l7) << 4), ow[h][0], ow[h][1], ow[h][2], ow[h][3]);
      asm volatile("fence.proxy.async.shared::cta;" ::: "memory");
      __syncwarp();
      if (lane == 0) {
        tma_store_2d(&tm_os, os, hg * 64, rt * 128 + warp * 16);
        asm volatile("cp.async.bulk.wait_group 0;" ::: "memory");
        if (wg == 0) mbar_arrive(bar_qfree);
        fence_async_global();
        red_add(&g_ocnt[(rt * 2 + wg) * 8 + hg], 32u);
      }
      __syncwarp();
    }
    {
    float acc[64];
    if (wg == 0) {
      mbar_wait(bar_full2 + 24, 0);
      gv0 = ld_relaxed(&g_gate[row0]); gv1 = ld_relaxed(&g_gate[row0 + 8]);
    }
#pragma unroll 1
    for (int i = 8 * wg; i < 8; i++) {
      if (i == 0) mbar_wait(bar_ssm, 0);
      mbar_wait(bar_full2 + 8 * i, 0);
      const uint32_t sa = sb + o_off(i), sw = sb + w_off(i, 0), lbo = i < 6 ? BLK : PARK;
      wg_fence();
#pragma unroll
      for (int k = 0; k < 4; k++) wgmma_ss_n128(acc, make_desc(sa + k * 32, 16, 1024), make_desc(sw + k * 2048, lbo, 1024), (i | k) != 0);
      wg_commit();
      if (i == 0) {
        wg_wait<0>();
        if (lane == 0) mbar_arrive(bar_empty2);
      }
    }
    {
      const float g0 = __uint_as_float(gv0), g1 = __uint_as_float(gv1);
      const uint32_t h0 = pack2(1.f - g0, 1.f - g0), h1 = pack2(1.f - g1, 1.f - g1);
      wg_wait<0>();
      if (wg == 0) named_bar(2, 128);
      uint32_t ga[32];
#pragma unroll
      for (int j = 0; j < 32; j++) ga[j] = (j & 1) ? pack2(g1 * acc[2 * j], g1 * acc[2 * j + 1]) : pack2(g0 * acc[2 * j], g0 * acc[2 * j + 1]);
      const uint32_t ya = sb + 14 * BLK + ((mi >> 1) * 8 + l7) * 128 + (((2 * wq + (mi & 1)) ^ l7) << 4);
      const uint32_t ob = wg ? os : sb + 4 * BLK + wq * 2048;
      const uint32_t oa = ob + (l7 + (mi & 1) * 8) * 128;
      if (wg == 0) mbar_wait(bar_y, 0);
      uint32_t y[8][4];
#pragma unroll
      for (int np = 0; np < 8; np++) ldsm_x4_t(y[np][0], y[np][1], y[np][2], y[np][3], ya + np * 16 * 128);
#pragma unroll
      for (int np = 0; np < 8; np++)
        stsm_x4(oa + (wg ? 0 : (np >> 2) * BLK) + (((2 * (np & 3) + hi16) ^ l7) << 4), hfma2(h0, y[np][0], ga[4 * np]), hfma2(h1, y[np][1], ga[4 * np + 1]),
                hfma2(h0, y[np][2], ga[4 * np + 2]), hfma2(h1, y[np][3], ga[4 * np + 3]));
      asm volatile("fence.proxy.async.shared::cta;" ::: "memory");
      __syncwarp();
      if (lane == 0 && wg == 1) mbar_arrive(bar_qfree);
      if (lane == 0 && wg == 0) {
        tma_store_2d(&tm_out, ob, hg_in * 128, rt * 128 + hgblk * 64 + wq * 16);
        tma_store_2d(&tm_out, ob + BLK, hg_in * 128 + 64, rt * 128 + hgblk * 64 + wq * 16);
        asm volatile("cp.async.bulk.wait_group.read 0;" ::: "memory");
      }
    }
    }
  }
}

typedef CUresult (*EncodeFn)(CUtensorMap*, CUtensorMapDataType, cuuint32_t, void*, const cuuint64_t*, const cuuint64_t*,
                             const cuuint32_t*, const cuuint32_t*, CUtensorMapInterleave, CUtensorMapSwizzle,
                             CUtensorMapL2promotion, CUtensorMapFloatOOBfill);

void make_map(EncodeFn fn, CUtensorMap* m, const void* p, uint64_t cols, uint64_t rows, uint32_t bc, uint32_t br,
              CUtensorMapSwizzle sw = CU_TENSOR_MAP_SWIZZLE_128B) {
  cuuint64_t dims[2] = {cols, rows};
  cuuint64_t strides[1] = {cols * 2};
  cuuint32_t box[2] = {bc, br};
  cuuint32_t es[2] = {1, 1};
  fn(m, CU_TENSOR_MAP_DATA_TYPE_BFLOAT16, 2, const_cast<void*>(p), dims, strides, box, es, CU_TENSOR_MAP_INTERLEAVE_NONE,
     sw, CU_TENSOR_MAP_L2_PROMOTION_L2_128B, CU_TENSOR_MAP_FLOAT_OOB_FILL_NONE);
}

}

extern "C" void kernel_launch(void* const* d_in, const int* in_sizes, int n_in, void* d_out, int out_size) {
  (void)in_sizes; (void)n_in; (void)out_size;
  static EncodeFn fn = nullptr;
  static void* optr = nullptr;
  static void* xptr = nullptr;
  if (!fn) {
    void* p = nullptr;
    cudaDriverEntryPointQueryResult st;
    cudaGetDriverEntryPoint("cuTensorMapEncodeTiled", &p, cudaEnableDefault, &st);
    fn = (EncodeFn)p;
    cudaGetSymbolAddress(&optr, g_o);
    cudaGetSymbolAddress(&xptr, g_xT);
    cudaFuncSetAttribute(fused_kernel, cudaFuncAttributeMaxDynamicSharedMemorySize, SMEM_BYTES);
  }
  typedef const __nv_bfloat16* bp;
  CUtensorMap tx, tw, two, to, tos, tol, txs, txl;
  make_map(fn, &tx, d_in[0], 512, 2048, 64, 128);
  make_map(fn, &tw, d_in[1], 1536, 512, 64, 64);
  make_map(fn, &two, d_in[3], 512, 512, 64, 64);
  make_map(fn, &to, d_out, 512, 2048, 64, 16);
  make_map(fn, &tos, optr, 512, 2048, 64, 16);
  make_map(fn, &tol, optr, 512, 2048, 64, 64);
  make_map(fn, &txs, xptr, 2048, 512, 32, 64, CU_TENSOR_MAP_SWIZZLE_64B);
  make_map(fn, &txl, xptr, 16, 65536, 16, 128, CU_TENSOR_MAP_SWIZZLE_32B);
  fused_kernel<<<NCTA, 512, SMEM_BYTES, cudaStreamPerThread>>>(
      tx, tw, two, to, tos, tol, txs, txl, (bp)d_in[0], (bp)d_in[2], (bp)d_in[5], (bp)d_in[6], (bp)d_in[7], (bp)d_in[8], (bp)d_in[9],
      (bp)d_in[10], (bp)d_in[11]);
}
```
